```python
import torch

def _softmax(x, axis=-1):
    return torch.softmax(x, dim=axis)

def _gelu(x):
    return torch.nn.functional.gelu(x, approximate='tanh')

def _silu(x):
    return torch.nn.functional.silu(x)

def _sigmoid(x):
    return torch.sigmoid(x)

def _layernorm(x, axis=-1, eps=1e-05):
    m = x.mean(dim=axis, keepdim=True)
    v = x.var(dim=axis, keepdim=True, unbiased=False)
    return (x - m) / torch.sqrt(v + eps)

def _scatter_add(tgt, idx, src, axis=0):
    return tgt.clone().index_add_(axis, idx, src)

def _segment_sum(src, seg, n):
    out = torch.zeros((n,) + src.shape[1:], dtype=src.dtype)
    return out.index_add_(0, seg, src)

def _pad(x, pw):
    flat = tuple((v for pair in reversed(pw) for v in pair))
    return torch.nn.functional.pad(x, flat)
kernel_name = 'adaLN_cond__memory_aug_recurrent_mem_tr__dense_activation_gelu__prompt'

def setup_inputs():

    _w = lambda a: (lambda t: t.to(torch.bfloat16) if t.is_floating_point() else t)(torch.as_tensor(a))

    def _A_setup():
        B, S, Dm = (1, 2048, 1024)
        H, Dh = (32, 128)
        M, seg = (8, 32)
        seg = min(seg, S)
        S = S // seg * seg
        return {'x': _w((lambda *s: torch.randn(*s, dtype=torch.bfloat16) * 0.05)(B, S, Dm)), 'mem0': _w((lambda *s: torch.randn(*s, dtype=torch.bfloat16) * 0.8)(B, M, Dm)), 'Wq': _w((lambda *s: torch.randn(*s, dtype=torch.bfloat16) * 1.6)(Dm, H, Dh) * Dm ** (-0.5)), 'Wk': _w((lambda *s: torch.randn(*s, dtype=torch.bfloat16) * 1.6)(Dm, H, Dh) * Dm ** (-0.5)), 'Wv': _w((lambda *s: torch.randn(*s, dtype=torch.bfloat16) * 0.8)(Dm, H, Dh) * Dm ** (-0.5)), 'Wo': _w((lambda *s: torch.randn(*s, dtype=torch.bfloat16) * 0.8)(H, Dh, Dm) * (H * Dh) ** (-0.5)), 'seg_len': seg}
    _A_in = _A_setup()

    def _B_setup():
        B, S, D, F = (1, 2048, 1024, 3584)
        return {'x': _w((lambda *s: torch.randn(*s, dtype=torch.bfloat16) * 0.05)(B, S, D)), 'w1': _w((lambda *s: torch.randn(*s, dtype=torch.bfloat16) * 1.6)(D, F) * D ** (-0.5)), 'b1': _w((lambda *s: torch.randn(*s, dtype=torch.bfloat16) * 1.6)(F) * 0.01), 'w2': _w((lambda *s: torch.randn(*s, dtype=torch.bfloat16) * 0.2)(F, D) * F ** (-0.5)), 'b2': _w((lambda *s: torch.randn(*s, dtype=torch.bfloat16) * 0.2)(D) * 0.01)}
    _B_in = _B_setup()
    return {'A_x': _A_in['x'], 'A_mem0': _A_in['mem0'], 'A_Wq': _A_in['Wq'], 'A_Wk': _A_in['Wk'], 'A_Wv': _A_in['Wv'], 'A_Wo': _A_in['Wo'], 'A_seg_len': _A_in['seg_len'], 'B_x': _B_in['x'], 'B_w1': _B_in['w1'], 'B_b1': _B_in['b1'], 'B_w2': _B_in['w2'], 'B_b2': _B_in['b2'], 'c': _w((lambda *s: torch.randn(*s, dtype=torch.bfloat16) * 0.05)(1, 1024) * 8.0), 'w_mod': _w((lambda *s: torch.randn(*s, dtype=torch.bfloat16) * 0.05)(1024, 6 * 1024) * 1024 ** (-0.5) * 8.0)}

def reference(A_x, A_mem0, A_Wq, A_Wk, A_Wv, A_Wo, A_seg_len, B_x, B_w1, B_b1, B_w2, B_b2, c, w_mod):

    def _A_ref(x, mem0, Wq, Wk, Wv, Wo, seg_len):
        B, S, Dm = x.shape
        H, Dh = (Wq.shape[1], Wq.shape[2])
        M = mem0.shape[1]
        scale = Dh ** (-0.5)
        n_seg = S // seg_len
        L = M + seg_len
        idx = torch.arange(L)
        mask = (idx[:, None] < M) | (idx[:, None] >= idx[None, :])
        mem = mem0
        outs = []
        for s in range(n_seg):
            xs = x[:, s * seg_len:(s + 1) * seg_len, :].clone()
            h = torch.concatenate([mem, xs], axis=1)
            q = torch.einsum('btd,dhe->bhte', h, Wq)
            k = torch.einsum('btd,dhe->bhte', h, Wk)
            v = torch.einsum('btd,dhe->bhte', h, Wv)
            scores = torch.einsum('bhqe,bhke->bhqk', q, k) * scale
            scores = torch.where(mask[None, None], scores, -1000000000.0)
            p = _softmax(scores, axis=-1)
            o = torch.einsum('bhqk,bhke->bhqe', p, v)
            o = torch.einsum('bhte,hed->btd', o, Wo)
            mem = o[:, :M, :].clone()
            outs.append(o[:, M:, :])
        return torch.concatenate(outs, axis=1)

    def _B_ref(x, w1, b1, w2, b2):
        h = torch.einsum('bsd,df->bsf', x, w1) + b1
        h = _gelu(h)
        return torch.einsum('bsf,fd->bsd', h, w2) + b2
    x = A_x
    mod = (_silu(c) @ w_mod).reshape(c.shape[0], 6, 1, -1)
    sa, ca, ga, sb, cb, gb = (mod[:, 0].clone(), mod[:, 1].clone(), mod[:, 2].clone(), mod[:, 3].clone(), mod[:, 4].clone(), mod[:, 5].clone())
    h = _layernorm(x, axis=-1) * (1 + ca) + sa
    x = x + ga * _A_ref(h, A_mem0, A_Wq, A_Wk, A_Wv, A_Wo, A_seg_len)
    h = _layernorm(x, axis=-1) * (1 + cb) + sb
    x = x + gb * _B_ref(h, B_w1, B_b1, B_w2, B_b2)
    return x
```

```cpp
#include <cuda_runtime.h>
#include <cuda.h>
#include <cuda_bf16.h>
#include <stdint.h>

typedef __nv_bfloat16 bf16;

__device__ __align__(16) float g_mod[6144];
__device__ __align__(1024) uint4 g_modp[4 * 512];
__device__ __align__(128) uint4 g_hsm[8];
__device__ __align__(128) unsigned g_fcnt_[32];
__device__ __align__(128) uint4 g_hprog_[8];
#define g_fcnt g_fcnt_[0]
#define g_hprog g_hprog_[0]
__device__ __align__(1024) uint4 g_h[2048 * 1024 / 8];
__device__ __align__(1024) uint4 g_O[2048 * 4096 / 8];
__device__ __align__(1024) uint4 g_h2[2048 * 1024 / 8];
__device__ __align__(1024) uint4 g_xp[2048 * 1024 / 8];
__device__ __align__(1024) unsigned g_oc[2 * 16 * 32];
__device__ __align__(1024) uint4 g_stat[2048 * 4];
__device__ __align__(1024) unsigned g_cnt[16 * 4 * 32];
__device__ __align__(1024) uint4 g_ar[160 * 64];
__device__ __align__(1024) uint4 g_xc[33 * 16384];
__device__ __align__(1024) unsigned g_tm[128 * 8];
#define PH(i)
#define FT(i)
#define PT(i)
#define PTT(i, t)
#define PDUMP()
#define PZERO()
#define FC(i)
#define RP(i)
#define RPN(i, s)
#define TSV(i, v)
#define TS(i)

#define FTS_ 0
#define NB1 2
#define NB2 3
#define IB2 14
#define IB3 11
#define IV 3
#define LD1 1000
#define LD2 800
#define LD3 8000
#define VDL 100
#define GT 12
#define HPS 400
#define HPR 512
#define HPW 2
#define PDS 2
#define VW 0
#define NH 3
#define NWA 7
#define NWB 7
#define VO 8
#define VE 0
#define WPC 2
#define WPA 2
#define LG 1
#define NCS 1
#define PSO 0
#define NWQ 9
#define ASM 1
#define W3P 0
#define AT8 1
#define TMP 1
#define WPF 0
#define HREL "relaxed"
constexpr int WIN = 2, RF_ = 208, RA_ = 488 - 2 * RF_;
#define SPIN_LIMIT (1 << 20)
__device__ __forceinline__ uint64_t mkdesc(uint32_t addr, uint32_t lbo, uint32_t sbo) {
  return (uint64_t)((addr & 0x3FFFF) >> 4) | ((uint64_t)(lbo >> 4) << 16) | ((uint64_t)(sbo >> 4) << 32) | (1ull << 62);
}
__device__ __forceinline__ void mbar_init(uint32_t a, int c) { asm volatile("mbarrier.init.shared.b64 [%0],%1;" ::"r"(a), "r"(c) : "memory"); }
__device__ __forceinline__ void mbar_wait(uint32_t a, uint32_t par) {
  asm volatile(
      "{.reg .pred p; .reg .u32 n;\n"
      "mov.u32 n, 0;\n"
      "W: mbarrier.try_wait.parity.shared.b64 p,[%0],%1;\n"
      "@p bra D;\n"
      "add.u32 n, n, 1;\n"
      "setp.lt.u32 p, n, %2;\n"
      "@p bra W;\n"
      "trap;\n"
      "D:}" ::"r"(a), "r"(par), "n"(SPIN_LIMIT) : "memory");
}
__device__ __forceinline__ void mbar_wait_q(uint32_t a, uint32_t par) {
  asm volatile(
      "{.reg .pred p; .reg .u32 n;\n"
      "mov.u32 n, 0;\n"
      "W: mbarrier.try_wait.parity.shared.b64 p,[%0],%1,4000;\n"
      "@p bra D;\n"
      "add.u32 n, n, 1;\n"
      "setp.lt.u32 p, n, %2;\n"
      "@p bra W;\n"
      "trap;\n"
      "D:}" ::"r"(a), "r"(par), "n"(SPIN_LIMIT / 16) : "memory");
}
__device__ __forceinline__ void mbar_expect(uint32_t a, uint32_t b) { asm volatile("mbarrier.arrive.expect_tx.shared.b64 _,[%0],%1;" ::"r"(a), "r"(b) : "memory"); }
__device__ __forceinline__ uint32_t mapa(uint32_t a, uint32_t cta) { uint32_t r; asm("mapa.shared::cluster.u32 %0,%1,%2;" : "=r"(r) : "r"(a), "r"(cta)); return r; }
__device__ __forceinline__ void mbar_arrive_cl(uint32_t a) { asm volatile("mbarrier.arrive.shared::cluster.b64 _,[%0];" ::"r"(a) : "memory"); }
__device__ __forceinline__ void tma2d(uint32_t dst, const CUtensorMap* m, int c0, int c1, uint32_t mb) {
  asm volatile("cp.async.bulk.tensor.2d.shared::cluster.global.mbarrier::complete_tx::bytes [%0],[%1,{%2,%3}],[%4];" ::"r"(dst), "l"(m), "r"(c0), "r"(c1), "r"(mb) : "memory");
}
__device__ __forceinline__ uint64_t pol_stream() { uint64_t p; asm("createpolicy.fractional.L2::evict_first.b64 %0, 1.0;" : "=l"(p)); return p; }
__device__ __forceinline__ void tma2d_s(uint32_t dst, const CUtensorMap* m, int c0, int c1, uint32_t mb) {
  asm volatile("cp.async.bulk.tensor.2d.shared::cluster.global.mbarrier::complete_tx::bytes.L2::cache_hint [%0],[%1,{%2,%3}],[%4],%5;" ::"r"(dst), "l"(m), "r"(c0), "r"(c1), "r"(mb), "l"(pol_stream()) : "memory");
}
__device__ __forceinline__ void tma2d_pf(const CUtensorMap* m, int c0, int c1) {
  asm volatile("cp.async.bulk.prefetch.tensor.2d.L2.global [%0,{%1,%2}];" ::"l"(m), "r"(c0), "r"(c1) : "memory");
}
template <bool STREAM = false>
__device__ __forceinline__ void e_expect_tma3d(uint32_t dst, const CUtensorMap* m, int c1, int c2, uint32_t mb, uint32_t bytes) {
  if (STREAM) asm volatile("{.reg .pred p; elect.sync _|p, 0xffffffff; @p mbarrier.arrive.expect_tx.shared.b64 _,[%4],%5;\n"
               "@p cp.async.bulk.tensor.3d.shared::cluster.global.mbarrier::complete_tx::bytes.L2::cache_hint [%0],[%1,{0,%2,%3}],[%4],%6;}" ::"r"(dst), "l"(m), "r"(c1), "r"(c2), "r"(mb), "r"(bytes), "l"(pol_stream()) : "memory");
  else asm volatile("{.reg .pred p; elect.sync _|p, 0xffffffff; @p mbarrier.arrive.expect_tx.shared.b64 _,[%4],%5;\n"
               "@p cp.async.bulk.tensor.3d.shared::cluster.global.mbarrier::complete_tx::bytes [%0],[%1,{0,%2,%3}],[%4];}" ::"r"(dst), "l"(m), "r"(c1), "r"(c2), "r"(mb), "r"(bytes) : "memory");
}
template <bool STREAM = false>
__device__ __forceinline__ void e_bulk_ld(uint32_t dst, const void* src, uint32_t n, uint32_t mb) {
  if (STREAM) asm volatile("{.reg .pred p; elect.sync _|p, 0xffffffff; @p cp.async.bulk.shared::cluster.global.mbarrier::complete_tx::bytes.L2::cache_hint [%0],[%1],%2,[%3],%4;}" ::"r"(dst), "l"(src), "r"(n), "r"(mb), "l"(pol_stream()) : "memory");
  else asm volatile("{.reg .pred p; elect.sync _|p, 0xffffffff; @p cp.async.bulk.shared::cluster.global.mbarrier::complete_tx::bytes [%0],[%1],%2,[%3];}" ::"r"(dst), "l"(src), "r"(n), "r"(mb) : "memory");
}
#define BULK_COMMIT() asm volatile("cp.async.bulk.commit_group;" ::: "memory")
#define BULK_WAIT_READ(n) asm volatile("cp.async.bulk.wait_group.read " #n ";" ::: "memory")
#define FENCE_ASYNC_SMEM() asm volatile("fence.proxy.async.shared::cta;" ::: "memory")
#define FENCE_ASYNC_G() asm volatile("fence.proxy.async.global;" ::: "memory")
#define WG_FENCE() asm volatile("wgmma.fence.sync.aligned;" ::: "memory")
#define WG_COMMIT() asm volatile("wgmma.commit_group.sync.aligned;" ::: "memory")
#define WG_WAIT(n) asm volatile("wgmma.wait_group.sync.aligned " #n ";" ::: "memory")
#define BAR_SYNC(id, n) asm volatile("bar.sync %0,%1;" ::"n"(id), "n"(n) : "memory")
#define BAR_ARRIVE(id, n) asm volatile("bar.arrive %0,%1;" ::"n"(id), "n"(n) : "memory")
#define SCHED_FENCE(k) asm volatile("{.reg .pred p; setp.ne.u32 p,%0,0; @p trap;}" ::"r"(mp.zero[(k) - 46]) : "memory")
#define CLUSTER_ARRIVE() asm volatile("fence.release.sync_restrict::shared::cta.cluster; barrier.cluster.arrive.relaxed.aligned;" ::: "memory")
#define CLUSTER_WAIT() asm volatile("barrier.cluster.wait.aligned;" ::: "memory")
#define CLUSTER_SYNC() do { CLUSTER_ARRIVE(); CLUSTER_WAIT(); } while (0)
__device__ __forceinline__ uint32_t pk(float lo, float hi) { uint32_t r; asm("cvt.rn.bf16x2.f32 %0,%1,%2;" : "=r"(r) : "f"(hi), "f"(lo)); return r; }
__device__ __forceinline__ float blo(uint32_t v) { return __uint_as_float(v << 16); }
__device__ __forceinline__ float bhi(uint32_t v) { return __uint_as_float(v & 0xffff0000u); }
__device__ __forceinline__ void ldsm4(uint32_t* r, uint32_t a) {
  asm volatile("ldmatrix.sync.aligned.m8n8.x4.shared.b16 {%0,%1,%2,%3},[%4];" : "=r"(r[0]), "=r"(r[1]), "=r"(r[2]), "=r"(r[3]) : "r"(a) : "memory");
}
__device__ __forceinline__ void ldsm4t(uint32_t* r, uint32_t a) {
  asm volatile("ldmatrix.sync.aligned.m8n8.x4.trans.shared.b16 {%0,%1,%2,%3},[%4];" : "=r"(r[0]), "=r"(r[1]), "=r"(r[2]), "=r"(r[3]) : "r"(a) : "memory");
}
__device__ __forceinline__ void ldsm4t_p(uint32_t* r, uint32_t a, uint32_t on) {
  if (!W3P) { ldsm4t(r, a); return; }
  asm volatile("{.reg .pred p; setp.ne.u32 p,%5,0; mov.b32 %0,%4; mov.b32 %1,%4; mov.b32 %2,%4; mov.b32 %3,%4; @p ldmatrix.sync.aligned.m8n8.x4.trans.shared.b16 {%0,%1,%2,%3},[%4];}" : "=&r"(r[0]), "=&r"(r[1]), "=&r"(r[2]), "=&r"(r[3]) : "r"(a), "r"(on) : "memory");
}
__device__ __forceinline__ void stsm4(uint32_t a, uint32_t r0, uint32_t r1, uint32_t r2, uint32_t r3) {
  asm volatile("stmatrix.sync.aligned.m8n8.x4.shared.b16 [%0],{%1,%2,%3,%4};" ::"r"(a), "r"(r0), "r"(r1), "r"(r2), "r"(r3) : "memory");
}
__device__ __forceinline__ void mma16(float* d, uint32_t a0, uint32_t a1, uint32_t a2, uint32_t a3, uint32_t b0, uint32_t b1) {
  asm volatile("mma.sync.aligned.m16n8k16.row.col.f32.bf16.bf16.f32 {%0,%1,%2,%3},{%4,%5,%6,%7},{%8,%9},{%0,%1,%2,%3};"
               : "+f"(d[0]), "+f"(d[1]), "+f"(d[2]), "+f"(d[3]) : "r"(a0), "r"(a1), "r"(a2), "r"(a3), "r"(b0), "r"(b1));
}
__device__ __forceinline__ void mma8(float* d, uint32_t a0, uint32_t a1, uint32_t b0) {
  asm volatile("mma.sync.aligned.m16n8k8.row.col.f32.bf16.bf16.f32 {%0,%1,%2,%3},{%4,%5},{%6},{%0,%1,%2,%3};"
               : "+f"(d[0]), "+f"(d[1]), "+f"(d[2]), "+f"(d[3]) : "r"(a0), "r"(a1), "r"(b0));
}
__device__ __forceinline__ float4 lds4f(uint32_t a) { float4 v; asm volatile("ld.shared.v4.f32 {%0,%1,%2,%3},[%4];" : "=f"(v.x), "=f"(v.y), "=f"(v.z), "=f"(v.w) : "r"(a) : "memory"); return v; }
__device__ __forceinline__ uint4 lds4(uint32_t a) { uint4 v; asm volatile("ld.shared.v4.u32 {%0,%1,%2,%3},[%4];" : "=r"(v.x), "=r"(v.y), "=r"(v.z), "=r"(v.w) : "r"(a) : "memory"); return v; }
__device__ __forceinline__ uint2 lds2u(uint32_t a) { uint2 v; asm volatile("ld.shared.v2.u32 {%0,%1},[%2];" : "=r"(v.x), "=r"(v.y) : "r"(a) : "memory"); return v; }
__device__ __forceinline__ uint32_t lds1(uint32_t a) { uint32_t v; asm volatile("ld.shared.u32 %0,[%1];" : "=r"(v) : "r"(a) : "memory"); return v; }
__device__ __forceinline__ void sts4(uint32_t a, uint32_t x, uint32_t y, uint32_t z, uint32_t w) { asm volatile("st.shared.v4.u32 [%0],{%1,%2,%3,%4};" ::"r"(a), "r"(x), "r"(y), "r"(z), "r"(w) : "memory"); }
__device__ __forceinline__ void sts1(uint32_t a, uint32_t x) { asm volatile("st.shared.u32 [%0],%1;" ::"r"(a), "r"(x) : "memory"); }
__device__ __forceinline__ void sta4(uint32_t a, const uint32_t* v, uint32_t mb) {
  asm volatile("st.async.shared::cluster.mbarrier::complete_tx::bytes.v4.b32 [%0],{%1,%2,%3,%4},[%5];" ::"r"(a), "r"(v[0]), "r"(v[1]), "r"(v[2]), "r"(v[3]), "r"(mb) : "memory");
}
__device__ __forceinline__ uint4 ldg_rlx4(const void* p) { uint4 v; asm volatile("ld.relaxed.gpu.global.v4.u32 {%0,%1,%2,%3},[%4];" : "=r"(v.x), "=r"(v.y), "=r"(v.z), "=r"(v.w) : "l"(p) : "memory"); return v; }
__device__ __forceinline__ uint4 ldg_b128(const void* p) {
  uint4 v;
  asm volatile("{.reg .b128 t; .reg .b64 a,b; ld.relaxed.gpu.global.b128 t,[%4]; mov.b128 {a,b},t; mov.b64 {%0,%1},a; mov.b64 {%2,%3},b;}" : "=r"(v.x), "=r"(v.y), "=r"(v.z), "=r"(v.w) : "l"(p) : "memory");
  return v;
}
__device__ __forceinline__ void stg_b128(void* p, uint32_t x, uint32_t y, uint32_t z, uint32_t w) {
  asm volatile("{.reg .b128 t; .reg .b64 a,b; mov.b64 a,{%1,%2}; mov.b64 b,{%3,%4}; mov.b128 t,{a,b}; st.relaxed.gpu.global.b128 [%0],t;}" ::"l"(p), "r"(x), "r"(y), "r"(z), "r"(w) : "memory");
}
__device__ __forceinline__ unsigned ld_acq(const unsigned* p) { unsigned v; asm volatile("ld.acquire.gpu.global.u32 %0,[%1];" : "=r"(v) : "l"(p) : "memory"); return v; }
__device__ __forceinline__ void wait_cnt(const unsigned* p, unsigned n) { int it = 0; while (ld_acq(p) < n) { if (++it > SPIN_LIMIT) __trap(); } }
__device__ __forceinline__ void wait_h(unsigned n) {
  int it = 0;
  while (true) {
    uint4 v;
    asm volatile("{.reg .b128 t; .reg .b64 a,b; ld.acquire.gpu.global.b128 t,[%4]; mov.b128 {a,b},t; mov.b64 {%0,%1},a; mov.b64 {%2,%3},b;}" : "=r"(v.x), "=r"(v.y), "=r"(v.z), "=r"(v.w) : "l"(&g_hprog) : "memory");
    if (min(min(v.x, v.y), min(v.z, v.w)) > n) break;
    if (++it > SPIN_LIMIT) __trap();
    __nanosleep(200);
  }
  FENCE_ASYNC_G();
}
__device__ __forceinline__ uint32_t clk() { uint32_t c; asm volatile("mov.u32 %0,%%clock;" : "=r"(c)); return c; }
__device__ __forceinline__ uint32_t gtime() { uint32_t c; asm volatile("mov.u32 %0,%%globaltimer_lo;" : "=r"(c)); return c; }
__device__ __forceinline__ void wait_until(uint32_t t0, uint32_t d) { while (clk() - t0 < d) {} }
__device__ __forceinline__ float ex2(float x) { float r; asm("ex2.approx.ftz.f32 %0,%1;" : "=f"(r) : "f"(x)); return r; }
__device__ __forceinline__ float silu(float x) { return __fdividef(x, 1.f + __expf(-x)); }
__device__ __forceinline__ float rbf(float x) { return __bfloat162float(__float2bfloat16_rn(x)); }

__device__ __forceinline__ void wgmma_ss_n128(float* d, uint64_t a, uint64_t b, int sd) {
  asm volatile("{.reg .pred p; setp.ne.b32 p, %66, 0;\n"
    "wgmma.mma_async.sync.aligned.m64n128k16.f32.bf16.bf16 {%0,%1,%2,%3,%4,%5,%6,%7,%8,%9,%10,%11,%12,%13,%14,%15,%16,%17,%18,%19,%20,%21,%22,%23,%24,%25,%26,%27,%28,%29,%30,%31,%32,%33,%34,%35,%36,%37,%38,%39,%40,%41,%42,%43,%44,%45,%46,%47,%48,%49,%50,%51,%52,%53,%54,%55,%56,%57,%58,%59,%60,%61,%62,%63}, %64, %65, p, 1, 1, 0, 1;}\n"
    : "+f"(d[0]),"+f"(d[1]),"+f"(d[2]),"+f"(d[3]),"+f"(d[4]),"+f"(d[5]),"+f"(d[6]),"+f"(d[7]),
      "+f"(d[8]),"+f"(d[9]),"+f"(d[10]),"+f"(d[11]),"+f"(d[12]),"+f"(d[13]),"+f"(d[14]),"+f"(d[15]),
      "+f"(d[16]),"+f"(d[17]),"+f"(d[18]),"+f"(d[19]),"+f"(d[20]),"+f"(d[21]),"+f"(d[22]),"+f"(d[23]),
      "+f"(d[24]),"+f"(d[25]),"+f"(d[26]),"+f"(d[27]),"+f"(d[28]),"+f"(d[29]),"+f"(d[30]),"+f"(d[31]),
      "+f"(d[32]),"+f"(d[33]),"+f"(d[34]),"+f"(d[35]),"+f"(d[36]),"+f"(d[37]),"+f"(d[38]),"+f"(d[39]),
      "+f"(d[40]),"+f"(d[41]),"+f"(d[42]),"+f"(d[43]),"+f"(d[44]),"+f"(d[45]),"+f"(d[46]),"+f"(d[47]),
      "+f"(d[48]),"+f"(d[49]),"+f"(d[50]),"+f"(d[51]),"+f"(d[52]),"+f"(d[53]),"+f"(d[54]),"+f"(d[55]),
      "+f"(d[56]),"+f"(d[57]),"+f"(d[58]),"+f"(d[59]),"+f"(d[60]),"+f"(d[61]),"+f"(d[62]),"+f"(d[63])
    : "l"(a), "l"(b), "r"(sd));
}
__device__ __forceinline__ void wgmma_ss_n192(float* d, uint64_t a, uint64_t b, int sd) {
  asm volatile("{.reg .pred p; setp.ne.b32 p, %98, 0;\n"
    "wgmma.mma_async.sync.aligned.m64n192k16.f32.bf16.bf16 {%0,%1,%2,%3,%4,%5,%6,%7,%8,%9,%10,%11,%12,%13,%14,%15,%16,%17,%18,%19,%20,%21,%22,%23,%24,%25,%26,%27,%28,%29,%30,%31,%32,%33,%34,%35,%36,%37,%38,%39,%40,%41,%42,%43,%44,%45,%46,%47,%48,%49,%50,%51,%52,%53,%54,%55,%56,%57,%58,%59,%60,%61,%62,%63,%64,%65,%66,%67,%68,%69,%70,%71,%72,%73,%74,%75,%76,%77,%78,%79,%80,%81,%82,%83,%84,%85,%86,%87,%88,%89,%90,%91,%92,%93,%94,%95}, %96, %97, p, 1, 1, 0, 1;}\n"
    : "+f"(d[0]),"+f"(d[1]),"+f"(d[2]),"+f"(d[3]),"+f"(d[4]),"+f"(d[5]),"+f"(d[6]),"+f"(d[7]),
      "+f"(d[8]),"+f"(d[9]),"+f"(d[10]),"+f"(d[11]),"+f"(d[12]),"+f"(d[13]),"+f"(d[14]),"+f"(d[15]),
      "+f"(d[16]),"+f"(d[17]),"+f"(d[18]),"+f"(d[19]),"+f"(d[20]),"+f"(d[21]),"+f"(d[22]),"+f"(d[23]),
      "+f"(d[24]),"+f"(d[25]),"+f"(d[26]),"+f"(d[27]),"+f"(d[28]),"+f"(d[29]),"+f"(d[30]),"+f"(d[31]),
      "+f"(d[32]),"+f"(d[33]),"+f"(d[34]),"+f"(d[35]),"+f"(d[36]),"+f"(d[37]),"+f"(d[38]),"+f"(d[39]),
      "+f"(d[40]),"+f"(d[41]),"+f"(d[42]),"+f"(d[43]),"+f"(d[44]),"+f"(d[45]),"+f"(d[46]),"+f"(d[47]),
      "+f"(d[48]),"+f"(d[49]),"+f"(d[50]),"+f"(d[51]),"+f"(d[52]),"+f"(d[53]),"+f"(d[54]),"+f"(d[55]),
      "+f"(d[56]),"+f"(d[57]),"+f"(d[58]),"+f"(d[59]),"+f"(d[60]),"+f"(d[61]),"+f"(d[62]),"+f"(d[63]),
      "+f"(d[64]),"+f"(d[65]),"+f"(d[66]),"+f"(d[67]),"+f"(d[68]),"+f"(d[69]),"+f"(d[70]),"+f"(d[71]),
      "+f"(d[72]),"+f"(d[73]),"+f"(d[74]),"+f"(d[75]),"+f"(d[76]),"+f"(d[77]),"+f"(d[78]),"+f"(d[79]),
      "+f"(d[80]),"+f"(d[81]),"+f"(d[82]),"+f"(d[83]),"+f"(d[84]),"+f"(d[85]),"+f"(d[86]),"+f"(d[87]),
      "+f"(d[88]),"+f"(d[89]),"+f"(d[90]),"+f"(d[91]),"+f"(d[92]),"+f"(d[93]),"+f"(d[94]),"+f"(d[95])
    : "l"(a), "l"(b), "r"(sd));
}
__device__ __forceinline__ void wgmma_ss_n256(float* d, uint64_t a, uint64_t b, int sd) {
  asm volatile("{.reg .pred p; setp.ne.b32 p, %130, 0;\n"
    "wgmma.mma_async.sync.aligned.m64n256k16.f32.bf16.bf16 {%0,%1,%2,%3,%4,%5,%6,%7,%8,%9,%10,%11,%12,%13,%14,%15,%16,%17,%18,%19,%20,%21,%22,%23,%24,%25,%26,%27,%28,%29,%30,%31,%32,%33,%34,%35,%36,%37,%38,%39,%40,%41,%42,%43,%44,%45,%46,%47,%48,%49,%50,%51,%52,%53,%54,%55,%56,%57,%58,%59,%60,%61,%62,%63,%64,%65,%66,%67,%68,%69,%70,%71,%72,%73,%74,%75,%76,%77,%78,%79,%80,%81,%82,%83,%84,%85,%86,%87,%88,%89,%90,%91,%92,%93,%94,%95,%96,%97,%98,%99,%100,%101,%102,%103,%104,%105,%106,%107,%108,%109,%110,%111,%112,%113,%114,%115,%116,%117,%118,%119,%120,%121,%122,%123,%124,%125,%126,%127}, %128, %129, p, 1, 1, 0, 1;}\n"
    : "+f"(d[0]),"+f"(d[1]),"+f"(d[2]),"+f"(d[3]),"+f"(d[4]),"+f"(d[5]),"+f"(d[6]),"+f"(d[7]),
      "+f"(d[8]),"+f"(d[9]),"+f"(d[10]),"+f"(d[11]),"+f"(d[12]),"+f"(d[13]),"+f"(d[14]),"+f"(d[15]),
      "+f"(d[16]),"+f"(d[17]),"+f"(d[18]),"+f"(d[19]),"+f"(d[20]),"+f"(d[21]),"+f"(d[22]),"+f"(d[23]),
      "+f"(d[24]),"+f"(d[25]),"+f"(d[26]),"+f"(d[27]),"+f"(d[28]),"+f"(d[29]),"+f"(d[30]),"+f"(d[31]),
      "+f"(d[32]),"+f"(d[33]),"+f"(d[34]),"+f"(d[35]),"+f"(d[36]),"+f"(d[37]),"+f"(d[38]),"+f"(d[39]),
      "+f"(d[40]),"+f"(d[41]),"+f"(d[42]),"+f"(d[43]),"+f"(d[44]),"+f"(d[45]),"+f"(d[46]),"+f"(d[47]),
      "+f"(d[48]),"+f"(d[49]),"+f"(d[50]),"+f"(d[51]),"+f"(d[52]),"+f"(d[53]),"+f"(d[54]),"+f"(d[55]),
      "+f"(d[56]),"+f"(d[57]),"+f"(d[58]),"+f"(d[59]),"+f"(d[60]),"+f"(d[61]),"+f"(d[62]),"+f"(d[63]),
      "+f"(d[64]),"+f"(d[65]),"+f"(d[66]),"+f"(d[67]),"+f"(d[68]),"+f"(d[69]),"+f"(d[70]),"+f"(d[71]),
      "+f"(d[72]),"+f"(d[73]),"+f"(d[74]),"+f"(d[75]),"+f"(d[76]),"+f"(d[77]),"+f"(d[78]),"+f"(d[79]),
      "+f"(d[80]),"+f"(d[81]),"+f"(d[82]),"+f"(d[83]),"+f"(d[84]),"+f"(d[85]),"+f"(d[86]),"+f"(d[87]),
      "+f"(d[88]),"+f"(d[89]),"+f"(d[90]),"+f"(d[91]),"+f"(d[92]),"+f"(d[93]),"+f"(d[94]),"+f"(d[95]),
      "+f"(d[96]),"+f"(d[97]),"+f"(d[98]),"+f"(d[99]),"+f"(d[100]),"+f"(d[101]),"+f"(d[102]),"+f"(d[103]),
      "+f"(d[104]),"+f"(d[105]),"+f"(d[106]),"+f"(d[107]),"+f"(d[108]),"+f"(d[109]),"+f"(d[110]),"+f"(d[111]),
      "+f"(d[112]),"+f"(d[113]),"+f"(d[114]),"+f"(d[115]),"+f"(d[116]),"+f"(d[117]),"+f"(d[118]),"+f"(d[119]),
      "+f"(d[120]),"+f"(d[121]),"+f"(d[122]),"+f"(d[123]),"+f"(d[124]),"+f"(d[125]),"+f"(d[126]),"+f"(d[127])
    : "l"(a), "l"(b), "r"(sd));
}
__device__ __forceinline__ void wgmma_rs_n32(float* d, const uint32_t* a, uint64_t b, int sd) {
  asm volatile("{.reg .pred p; setp.ne.b32 p, %21, 0;\n"
    "wgmma.mma_async.sync.aligned.m64n32k16.f32.bf16.bf16 {%0,%1,%2,%3,%4,%5,%6,%7,%8,%9,%10,%11,%12,%13,%14,%15}, {%16,%17,%18,%19}, %20, p, 1, 1, 0;}\n"
    : "+f"(d[0]),"+f"(d[1]),"+f"(d[2]),"+f"(d[3]),"+f"(d[4]),"+f"(d[5]),"+f"(d[6]),"+f"(d[7]),
      "+f"(d[8]),"+f"(d[9]),"+f"(d[10]),"+f"(d[11]),"+f"(d[12]),"+f"(d[13]),"+f"(d[14]),"+f"(d[15])
    : "r"(a[0]), "r"(a[1]), "r"(a[2]), "r"(a[3]), "l"(b), "r"(sd));
}
__device__ __forceinline__ void wgmma_ssT_n32(float* d, uint64_t a, uint64_t b, int sd) {
  asm volatile("{.reg .pred p; setp.ne.b32 p, %18, 0;\n"
    "wgmma.mma_async.sync.aligned.m64n32k16.f32.bf16.bf16 {%0,%1,%2,%3,%4,%5,%6,%7,%8,%9,%10,%11,%12,%13,%14,%15}, %16, %17, p, 1, 1, 1, 0;}\n"
    : "+f"(d[0]),"+f"(d[1]),"+f"(d[2]),"+f"(d[3]),"+f"(d[4]),"+f"(d[5]),"+f"(d[6]),"+f"(d[7]),
      "+f"(d[8]),"+f"(d[9]),"+f"(d[10]),"+f"(d[11]),"+f"(d[12]),"+f"(d[13]),"+f"(d[14]),"+f"(d[15])
    : "l"(a), "l"(b), "r"(sd));
}

__device__ __forceinline__ void wgmma_rs_n32_z(float* d, const uint32_t* a, uint64_t b) {
  asm volatile("{.reg .pred p; setp.ne.b32 p, 0, 0;\n"
    "wgmma.mma_async.sync.aligned.m64n32k16.f32.bf16.bf16 {%0,%1,%2,%3,%4,%5,%6,%7,%8,%9,%10,%11,%12,%13,%14,%15}, {%16,%17,%18,%19}, %20, p, 1, 1, 0;}\n"
    : "=f"(d[0]),"=f"(d[1]),"=f"(d[2]),"=f"(d[3]),"=f"(d[4]),"=f"(d[5]),"=f"(d[6]),"=f"(d[7]),
      "=f"(d[8]),"=f"(d[9]),"=f"(d[10]),"=f"(d[11]),"=f"(d[12]),"=f"(d[13]),"=f"(d[14]),"=f"(d[15])
    : "r"(a[0]), "r"(a[1]), "r"(a[2]), "r"(a[3]), "l"(b));
}

namespace rec {
constexpr int NVR = 5;
constexpr int NVS = 16 - NVR;
constexpr int NVP = 2;
constexpr int NWP = NWQ;
constexpr uint32_t WO = 0;
constexpr uint32_t XB = 65536;
constexpr uint32_t PK = XB + 32768;
constexpr uint32_t VN = PK + 24576;
constexpr uint32_t VX0 = VN + 4096;
constexpr uint32_t WVS = 131072;
constexpr uint32_t MEM = WVS + 2 * NVS * 2048;
constexpr uint32_t ARO = MEM + 10240;
constexpr uint32_t OB = ARO + 5120;
constexpr uint32_t QT = OB + 2048;
constexpr uint32_t KT = QT + 2048;
constexpr uint32_t RQ = KT + 6144;
constexpr uint32_t RK = RQ + 2048;
constexpr uint32_t SC = RK + 2048;
constexpr uint32_t OT = OB;
constexpr uint32_t SCT = 768, TFP = 9 * 128;
constexpr uint32_t TF = SC + 2 * SCT;
constexpr uint32_t PRE = MEM + 2 * NVR * 2048;
constexpr uint32_t TA = TF + 8 * TFP;
constexpr uint32_t RX = TA + 7168;
constexpr uint32_t VX1 = RX + 2048;
constexpr uint32_t BARS = VX1 + 4096;
constexpr uint32_t PACE = BARS + 18 * 8;
constexpr uint32_t SMEM = BARS + 512;
static_assert(PRE + 3072 <= TF, "staging");
constexpr int NW1 = NWA;
static_assert(SMEM <= 232448, "smem");
constexpr uint32_t T_MEM = 0, T_QK = 128, T_O = 256, T_WV = 384, T_WO = 512, T_AR = 640, T_PK = 768, T_VM = 896, T_RX = 1024;
constexpr int B_E = 2, B_SC = 3, B_S = 4, B_O = 5, B_F = 6, B_W = 7, B_C = 9, B_K = 10, B_H = 15, B_T0 = 0, B_Q = 1, B_S2 = 6, B_T2 = 9, B_P = 13, B_T = 14, B_R = 11, B_X = 12, B_V = 8;
constexpr int XC = 16384, X_RING = 131072, X_SC = 65536, X_TOK = 4096;
#define X_VX(i) (((i) >> 1) * 2048 + ((i) & 1) * 512)
#define X_VM(i) (X_VX(i) + 1024)
#define X_VRING(n) (((n) & 1) * X_RING + ((n) & 2) * 4096)
#define X_VTAG(n) ((((n) >> 2) + 1) & 1)
}
struct RecMaps { CUtensorMap wq, wk, wv, wo, ari, vx, wm, wm3, hst; int zero[40]; };

#define F_(x) __uint_as_float(x)
#define U_(x) __float_as_uint(x)
__device__ __forceinline__ void ar_fetch(uint32_t dst, const CUtensorMap* m, int slot, int half, uint32_t mb) {
  asm volatile("{.reg .pred p; elect.sync _|p, 0xffffffff; @p mbarrier.arrive.expect_tx.shared.b64 _,[%4],10240;\n"
               "@p cp.async.bulk.tensor.2d.shared::cluster.global.mbarrier::complete_tx::bytes [%0],[%1,{%2,%3}],[%4];\n"
               "@p cp.async.bulk.tensor.2d.shared::cluster.global.mbarrier::complete_tx::bytes [%0+5120],[%1,{%2,%5}],[%4];}"
               ::"r"(dst), "l"(m), "r"(slot * 64), "r"(half * 80), "r"(mb), "r"(half * 80 + 40) : "memory");
}
__device__ __forceinline__ uint4 exch_b128(void* p, uint32_t x, uint32_t y, uint32_t z, uint32_t w) {
  uint4 v;
  asm volatile("{.reg .b128 s, t; .reg .b64 a,b; mov.b64 a,{%5,%6}; mov.b64 b,{%7,%8}; mov.b128 s,{a,b}; atom.relaxed.gpu.global.exch.b128 t,[%4],s;"
               " mov.b128 {a,b},t; mov.b64 {%0,%1},a; mov.b64 {%2,%3},b;}" : "=r"(v.x), "=r"(v.y), "=r"(v.z), "=r"(v.w) : "l"(p), "r"(x), "r"(y), "r"(z), "r"(w) : "memory");
  return v;
}
#define CONSUME(v) do { if ((v) == 0x7fc12345u) sts1(sb + rec::BARS + 96, 0); } while (0)
__device__ __forceinline__ uint2 ldg_b64(const void* p) { uint2 v; asm volatile("{.reg .b64 t; ld.relaxed.gpu.global.b64 t,[%2]; mov.b64 {%0,%1},t;}" : "=r"(v.x), "=r"(v.y) : "l"(p) : "memory"); return v; }
__device__ __forceinline__ void stg_b64(void* p, uint32_t x, uint32_t y) { asm volatile("{.reg .b64 t; mov.b64 t,{%1,%2}; st.relaxed.gpu.global.b64 [%0],t;}" ::"l"(p), "r"(x), "r"(y) : "memory"); }
__device__ __forceinline__ uint32_t tagbad(uint32_t x, uint32_t y, uint32_t tag) { uint32_t r; asm("lop3.b32 %0,%1,%2,%3,0x7e;" : "=r"(r) : "r"(x), "r"(y), "r"(tag)); return r; }

__device__ __forceinline__ bool anybad(uint32_t a, uint32_t b, uint32_t c, uint32_t d, uint32_t e, uint32_t f, uint32_t g, uint32_t h, uint32_t tag) {
  uint32_t r;
  asm volatile("{.reg .b32 t,u,v,w; .reg .pred p; lop3.b32 t,%1,%2,%9,0x7e; lop3.b32 u,%3,%4,%9,0x7e; lop3.b32 v,%5,%6,%9,0x7e; lop3.b32 w,%7,%8,%9,0x7e;"
               " lop3.b32 t,t,u,v,0xfe; lop3.b32 t,t,w,1,0xa8; setp.ne.u32 p,t,0; vote.sync.any.pred p,p,0xffffffff; selp.u32 %0,1,0,p;}"
               : "=r"(r) : "r"(a), "r"(b), "r"(c), "r"(d), "r"(e), "r"(f), "r"(g), "r"(h), "r"(tag));
  return r;
}
__device__ __forceinline__ bool anybad(uint32_t a, uint32_t b, uint32_t c, uint32_t d, uint32_t tag) {
  uint32_t r;
  asm volatile("{.reg .b32 t,u; .reg .pred p; lop3.b32 t,%1,%2,%5,0x7e; lop3.b32 u,%3,%4,%5,0x7e;"
               " lop3.b32 t,t,u,1,0xa8; setp.ne.u32 p,t,0; vote.sync.any.pred p,p,0xffffffff; selp.u32 %0,1,0,p;}"
               : "=r"(r) : "r"(a), "r"(b), "r"(c), "r"(d), "r"(tag));
  return r;
}
#define BADS(r) anybad(r[0].x, r[0].y, r[1].x, r[1].y, r[2].x, r[2].y, r[3].x, r[3].y, tag)
constexpr float SCS = 0.08838834764831845f * 1.4426950408889634f / 16.f;
__device__ __forceinline__ uint32_t pkh(float lo, float hi, uint32_t tag) {
  uint32_t r;
  asm("{.reg .b32 t; cvt.rn.satfinite.f16x2.f32 t,%1,%2; lop3.b32 %0,t,0xfffffffe,%3,0xea;}" : "=r"(r) : "f"(hi), "f"(lo), "r"(tag));
  return r;
}
__device__ __forceinline__ uint32_t addh(uint32_t a, uint32_t b) { uint32_t r; asm("add.rn.f16x2 %0,%1,%2;" : "=r"(r) : "r"(a), "r"(b)); return r; }
__device__ __forceinline__ float hlo(uint32_t v) { float r; asm("{.reg .b16 a,b; mov.b32 {a,b},%1; cvt.f32.f16 %0,a;}" : "=f"(r) : "r"(v)); return r; }
__device__ __forceinline__ float hhi(uint32_t v) { float r; asm("{.reg .b16 a,b; mov.b32 {a,b},%1; cvt.f32.f16 %0,b;}" : "=f"(r) : "r"(v)); return r; }
__device__ __forceinline__ uint32_t ordh(uint32_t v) {
  uint32_t r;
  asm("{.reg .b32 m; prmt.b32 m,%1,0,0xbb99; lop3.b32 %0,%1,m,0x7fff7fff,0x78;}" : "=r"(r) : "r"(v));
  return r;
}
template <bool MASK>
__device__ __forceinline__ float4 softmax2(const uint2 (&r)[4], uint32_t mx, uint32_t my) {
  uint32_t x = addh(addh(r[0].x, r[1].x), addh(r[2].x, r[3].x)), y = addh(addh(r[0].y, r[1].y), addh(r[2].y, r[3].y)), k;
  if (MASK) x = addh(x, mx);
  y = addh(y, my);
  asm("max.f16x2 %0,%1,%2;" : "=r"(k) : "r"(x), "r"(y));
  k = ordh(k);
  const int k0 = __reduce_max_sync(~0u, (int)(k << 16)), k1 = __reduce_max_sync(~0u, (int)k);
  k = ordh(__byte_perm(k0, k1, 0x7632));
  const float m0 = hlo(k) * -16.f, m1 = hhi(k) * -16.f;
  return make_float4(ex2(fmaf(hlo(x), 16.f, m0)), ex2(fmaf(hhi(x), 16.f, m1)), ex2(fmaf(hlo(y), 16.f, m0)), ex2(fmaf(hhi(y), 16.f, m1)));
}
__device__ __forceinline__ char* mkp(uint32_t lo, uint32_t hi) { uint64_t r; asm("mov.b64 %0,{%1,%2};" : "=l"(r) : "r"(lo), "r"(hi)); return (char*)r; }
#define LO(p) ((uint32_t)(uint64_t)(p))
#define HI(p) ((uint32_t)((uint64_t)(p) >> 32))
__device__ __forceinline__ uint32_t addbf(uint32_t a, uint32_t b) { uint32_t r; asm("add.rn.bf16x2 %0,%1,%2;" : "=r"(r) : "r"(a), "r"(b)); return r; }
__device__ __forceinline__ void pv_mem(const uint32_t (&p)[4], uint32_t pm, const uint4 (&v)[4], const uint4 (&vn)[2], uint32_t (&O)[4], uint32_t sums, uint32_t l16) {
  float o[4][4] = {{0, 0, 0, 0}, {0, 0, 0, 0}, {0, 0, 0, 0}, {0, 0, 0, 0}}, sum[4] = {0, 0, 0, 0};
  const uint32_t one = 0x3f803f80u;
  if (ASM) mma8(sum, one, one, pm);
  mma16(o[0], v[0].x, v[0].y, v[0].z, v[0].w, p[0], p[1]);
  mma16(o[1], v[2].x, v[2].y, v[2].z, v[2].w, p[0], p[1]);
  mma16(o[2], v[1].x, v[1].y, v[1].z, v[1].w, p[2], p[3]);
  mma16(o[3], v[3].x, v[3].y, v[3].z, v[3].w, p[2], p[3]);
  if (ASM) mma16(sum, one, one, one, one, p[0], p[1]);
  mma16(o[0], vn[0].x, vn[0].y, vn[0].z, vn[0].w, pm, pm);
  mma16(o[1], vn[1].x, vn[1].y, vn[1].z, vn[1].w, pm, pm);
  if (ASM) {
    mma16(sum, one, one, one, one, p[2], p[3]);
    asm volatile("{.reg .pred p; .reg .b32 t; and.b32 t,%3,0x1c0; setp.eq.u32 p,t,0; @p st.shared.v2.f32 [%0],{%1,%2};}" ::"r"(sums), "f"(sum[0]), "f"(sum[1]), "r"(l16) : "memory");
  }
  O[0] = pk(o[0][0] + o[2][0], o[0][1] + o[2][1]); O[1] = pk(o[0][2] + o[2][2], o[0][3] + o[2][3]);
  O[2] = pk(o[1][0] + o[3][0], o[1][1] + o[3][1]); O[3] = pk(o[1][2] + o[3][2], o[1][3] + o[3][3]);
}
__device__ __forceinline__ void pv_tok(const uint32_t (&p)[4], uint32_t pm, const uint4 (&v)[4], const uint32_t (&vm)[4], uint32_t (&O)[4]) {
  float o[2][4] = {{0, 0, 0, 0}, {0, 0, 0, 0}}, sum[4] = {0, 0, 0, 0};
  const uint32_t one = 0x3f803f80u;
  mma16(sum, one, one, one, one, p[0], p[1]);
  mma16(o[0], v[0].x, v[0].y, v[0].z, v[0].w, p[0], p[1]);
  mma16(o[1], v[2].x, v[2].y, v[2].z, v[2].w, p[0], p[1]);
  mma16(sum, one, one, one, one, p[2], p[3]);
  mma16(o[0], v[1].x, v[1].y, v[1].z, v[1].w, p[2], p[3]);
  mma16(o[1], v[3].x, v[3].y, v[3].z, v[3].w, p[2], p[3]);
  mma8(sum, one, one, pm);
  mma8(o[0], vm[0], vm[1], pm);
  mma8(o[1], vm[2], vm[3], pm);
  float i0, i1;
  asm("rcp.approx.ftz.f32 %0,%1;" : "=f"(i0) : "f"(sum[0]));
  asm("rcp.approx.ftz.f32 %0,%1;" : "=f"(i1) : "f"(sum[1]));
  O[0] = pk(o[0][0] * i0, o[0][1] * i1); O[1] = pk(o[0][2] * i0, o[0][3] * i1);
  O[2] = pk(o[1][0] * i0, o[1][1] * i1); O[3] = pk(o[1][2] * i0, o[1][3] * i1);
}
template <int OFF>
__device__ __forceinline__ void sta1(uint32_t a, uint32_t v, uint32_t mb) {
  asm volatile("st.async.shared::cluster.mbarrier::complete_tx::bytes.b32 [%0+%3],%1,[%2];" ::"r"(a), "r"(v), "r"(mb), "n"(OFF) : "memory");
}

__device__ __forceinline__ void rec_helper(char* smem, const bf16* x, const bf16* cvec, const CUtensorMap* wm) {
  const int tid = threadIdx.x, hb = blockIdx.x & 3;
  float4* md = (float4*)(smem + 12288);
  uint4* hs = (uint4*)(smem + 152 * 1024);
  uint4 xr[8];
  const uint4* px = (const uint4*)(x + (size_t)(hb * 16 + (tid >> 5) * 2) * 1024) + (tid & 31);
#pragma unroll
  for (int i = 0; i < 8; i++) xr[i] = __ldg(px + i * 32);
#pragma unroll 1
  for (int i = tid; i < 2560; i += 256) g_ar[hb * 2560 + i] = make_uint4(0, 0, 0, 0);
  g_tm[tid] = 0;
  g_oc[hb * 256 + tid] = 0;
  float4 mr[16];
#pragma unroll 1
  for (int k = 0; k < 32; k++) {
    float v[2][32], m[8] = {}, q[8] = {};
#pragma unroll
    for (int i = 0; i < 8; i++) {
      const uint4 u = xr[i];
      float* w = v[i >> 2] + (i & 3) * 8;
      w[0] = blo(u.x); w[1] = bhi(u.x); w[2] = blo(u.y); w[3] = bhi(u.y); w[4] = blo(u.z); w[5] = bhi(u.z); w[6] = blo(u.w); w[7] = bhi(u.w);
      xr[i] = __ldg(px + min(k + 1, 31) * 8192 + i * 32);
    }
#pragma unroll
    for (int i = 0; i < 64; i++) m[i & 7] += v[i & 1][i >> 1];
    m[0] = (m[0] + m[2]) + (m[4] + m[6]); m[1] = (m[1] + m[3]) + (m[5] + m[7]);
#pragma unroll
    for (int o = 16; o; o >>= 1) { m[0] += __shfl_xor_sync(~0u, m[0], o); m[1] += __shfl_xor_sync(~0u, m[1], o); }
    m[0] *= 1.f / 1024; m[1] *= 1.f / 1024;
#pragma unroll
    for (int i = 0; i < 64; i++) { float& w = v[i & 1][i >> 1]; w -= m[i & 1]; q[i & 7] += w * w; }
    q[0] = (q[0] + q[2]) + (q[4] + q[6]); q[1] = (q[1] + q[3]) + (q[5] + q[7]);
#pragma unroll
    for (int o = 16; o; o >>= 1) { q[0] += __shfl_xor_sync(~0u, q[0], o); q[1] += __shfl_xor_sync(~0u, q[1], o); }
    const float rstd[2] = {rsqrtf(q[0] * (1.f / 1024) + 1e-5f), rsqrtf(q[1] * (1.f / 1024) + 1e-5f)};
    if (k == 0) {
      PT(44);
#pragma unroll 1
      for (int i = 0; i < 2; i++) {
        uint4 p[4];
        int it = 0;
        while (true) {
#pragma unroll
          for (int u = 0; u < 4; u++) p[u] = ldg_rlx4(g_modp + u * 512 + i * 256 + tid);
          uint32_t ok = 1;
#pragma unroll
          for (int u = 0; u < 4; u++) ok &= p[u].x & p[u].y & p[u].z & p[u].w;
          if (__all_sync(~0u, ok)) break;
          if (++it > SPIN_LIMIT) __trap();
          __nanosleep(100);
        }
        md[i * 256 + tid] = make_float4(i + rbf((F_(p[0].x) + F_(p[1].x)) + (F_(p[2].x) + F_(p[3].x))), i + rbf((F_(p[0].y) + F_(p[1].y)) + (F_(p[2].y) + F_(p[3].y))),
                                        i + rbf((F_(p[0].z) + F_(p[1].z)) + (F_(p[2].z) + F_(p[3].z))), i + rbf((F_(p[0].w) + F_(p[1].w)) + (F_(p[2].w) + F_(p[3].w))));
      }
      BAR_SYNC(rec::B_F, 256);
#pragma unroll
      for (int i = 0; i < 16; i++) mr[i] = md[(i >> 3) * 256 + ((i >> 1) & 3) * 64 + (tid & 31) * 2 + (i & 1)];
      PT(45);
    }
#pragma unroll
    for (int i = 0; i < 4; i++) {
      const int ch = i * 32 + (tid & 31);
      const float4 s0 = mr[i * 2], s1 = mr[i * 2 + 1], c0 = mr[8 + i * 2], c1 = mr[9 + i * 2];
#pragma unroll
      for (int r = 0; r < 2; r++) {
        const int row = (tid >> 5) * 2 + r;
        const float* w = v[r] + i * 8;
        hs[(k & 1) * 2048 + (ch >> 3) * 128 + row * 8 + ((ch & 7) ^ (row & 7))] =
            make_uint4(pk(w[0] * rstd[r] * c0.x + s0.x, w[1] * rstd[r] * c0.y + s0.y), pk(w[2] * rstd[r] * c0.z + s0.z, w[3] * rstd[r] * c0.w + s0.w),
                       pk(w[4] * rstd[r] * c1.x + s1.x, w[5] * rstd[r] * c1.y + s1.y), pk(w[6] * rstd[r] * c1.z + s1.z, w[7] * rstd[r] * c1.w + s1.w));
      }
    }
    if (k == 0) PT(63);
    FENCE_ASYNC_SMEM();
    BAR_SYNC(rec::B_W, 288);
    if (k < 2) PT(46 + k * 12);
  }
  PT(59);
  PDUMP();
  const uint32_t sc = (uint32_t)__cvta_generic_to_shared(smem), wb = sc + 20480, mb = sc + rec::PACE;
#pragma unroll 1
  for (int i = tid; i < 512; i += 256) sts1(sc + i * 4, pk(silu(__bfloat162float(cvec[2 * i])), silu(__bfloat162float(cvec[2 * i + 1]))));
#pragma unroll 1
  for (int i = tid; i < 2048; i += 256) g_stat[hb * 2048 + i] = make_uint4(~0u, ~0u, ~0u, ~0u);
#pragma unroll 1
  for (int i = tid; i < 512; i += 256) g_cnt[hb * 512 + i] = 0;
  if (tid == 0 && hb == 0) g_fcnt = 0;
  if (tid == 0) asm volatile("{.reg .u32 t; mov.u32 t,%%smid; st.global.u32 [%0],t;}" ::"l"((unsigned*)g_hsm + hb) : "memory");
  BAR_SYNC(rec::B_O, 320);
  if (tid == 0) FT(37);
  const int lane = tid & 31;
  const uint32_t fa = wb + (tid >> 5) * 8192 + ((lane & 7) + (lane >> 4) * 8) * 128 + ((((lane >> 3) & 1) ^ (lane & 7)) << 4);
  float acc[2][4][4] = {};
#pragma unroll 1
  for (int i2 = -2; i2 < 32; i2 += 2) {
#pragma unroll
    for (int u = 0; u < 2; u++) {
      const int i = i2 + u;
      if (i < 30 && tid < 32) e_expect_tma3d<true>(wb + (i + 2) % 3 * 65536, wm, (i2 + 2) * 32, 32 + hb * 16 + u * 8, mb + (i + 2) % 3 * 8, 65536);
      if (i < 0) continue;
      mbar_wait(mb + i % 3 * 8, i / 3 & 1);
#pragma unroll
      for (int ks = 0; ks < 4; ks++) {
        const uint32_t b0 = lds1(sc + i2 * 64 + ks * 32 + (lane & 3) * 4), b1 = lds1(sc + i2 * 64 + ks * 32 + (lane & 3) * 4 + 16);
#pragma unroll
        for (int m = 0; m < 4; m++) {
          uint32_t a[4];
          ldsm4t(a, (fa ^ (m * 32)) + i % 3 * 65536 + ks * 2048);
          mma16(acc[u][m], a[0], a[1], a[2], a[3], b0, b1);
        }
      }
      FENCE_ASYNC_SMEM();
      BAR_SYNC(rec::B_F, 256);
    }
  }
  if (!(lane & 3)) {
#pragma unroll
    for (int i = 0; i < 16; i++) g_mod[2048 + hb * 1024 + (i >> 3) * 512 + (tid >> 5) * 64 + (i & 7) * 8 + (lane >> 2)] = rbf(acc[i >> 3][(i >> 1) & 3][(i & 1) * 2]);
  }
  BAR_SYNC(rec::B_F, 256);
  if (tid == 0) asm volatile("fence.acq_rel.gpu; griddepcontrol.launch_dependents;" ::: "memory");
  if (tid == 0) FT(33);
}

__global__ void __cluster_dims__(2, 1, 1) __launch_bounds__(512, 1)
k_rec(const __grid_constant__ RecMaps mp, const bf16* __restrict__ mem0, const bf16* __restrict__ x, const bf16* __restrict__ cvec,
      const bf16* __restrict__ wmod, const bf16* __restrict__ wo_g, char* xc, int dF, int dA, int dS, int dM, int dG, int dP, int dX, int dD, int dZ, int dZ2, int dV, int dX2) {
  using namespace rec;
  extern __shared__ __align__(1024) char smem[];
  const uint32_t sb = (uint32_t)__cvta_generic_to_shared(smem);
  if ((sb & 0x3FFFF) != 1024) __trap();
  PH(0);
  PZERO();
  if (threadIdx.x == 0) {
    int b = blockIdx.x;
    if (b >= 8 && b < 128) {
      const int t = (b >> 1) - 4, u = t - 32;
      b = 2 * (t < 32 ? 4 + (t & 16) + (t & 7) * 2 + ((t >> 3) & 1) : 36 + (u / 14) * 14 + (u % 7) * 2 + ((u / 7) & 1)) + (b & 1);
    }
    sts1(sb + rec::PACE + 24, b);
  }
#define ROLE_REFRESH { asm volatile("mov.u32 %0,%%tid.x;" : "=r"(tid)); wid = __shfl_sync(~0u, tid >> 5, 0); b = __shfl_sync(~0u, lds1(sb + PACE + 24), 0); }
#define ROLE_VARS int tid; asm volatile("mov.u32 %0,%%tid.x;" : "=r"(tid)); \
    int wid = __shfl_sync(~0u, tid >> 5, 0), b = __shfl_sync(~0u, lds1(sb + PACE + 24), 0);
#define wg (wid >> 2)
#define iw (wid & 3)
#define h (b >> 2)
#define j (b & 3)
#define a (b & 1)
#define bb ((b >> 1) & 1)
  const uint32_t wbar = sb + BARS + 48, obar = wbar + 8;
  if (threadIdx.x == 256) {
    for (int i = 0; i < 18; i++) if (i != 12) mbar_init(sb + BARS + i * 8, i == 3 || i == 8 || i == 9 || i == 10 ? 2 : 1);
    for (int i = 0; i < 3; i++) mbar_init(sb + PACE + i * 8, 1);
    asm volatile("fence.mbarrier_init.release.cluster;" ::: "memory");
    FENCE_ASYNC_SMEM();
    mbar_expect(sb + BARS, 2048);
    mbar_expect(sb + BARS + 16, 4096);
    mbar_expect(sb + BARS + 32, 4096);
    mbar_expect(sb + BARS + 40, 4096);
  }
  __syncthreads();
#define lane ((int)(l16 >> 4))
#define l16 (L16 & 0x1f0)
#define PIN(x) __shfl_xor_sync(~0u, (uint32_t)(x), 0)
#define lpub ((L16 & 0x30) * 64 + ((L16 >> 3) & 0x38))
#define lrow ((L16 & 0x70) + (((L16 >> 3) ^ L16) & 0x70 & ~((L16 >> 3) & 0x40) ? L16 & 0x180 : 512))

  const int role = __shfl_sync(~0u, threadIdx.x >> 7, 0);
  if (role < 2) {
    asm volatile("setmaxnreg.inc.sync.aligned.u32 %0;" ::"n"(RF_));
    if (blockIdx.x >= 128) { rec_helper(smem, x, cvec, &mp.wm3); return; }
    ROLE_VARS
    uint32_t L16 = __shfl_sync(~0u, sb + (tid & 31) * 16, tid & 31);
    {
      uint4 wm[8];
      const uint4* pw = (const uint4*)(wmod + (size_t)((b >> 5) * 256 + (tid >> 3)) * 6144 + (b & 31) * 64) + (tid & 7);
      const float cs = __bfloat162float(cvec[(b >> 5) * 256 + tid]);
#pragma unroll
      for (int i = 0; i < 8; i++) wm[i] = __ldcs(pw + (size_t)i * 32 * 768);
      float* sc = (float*)(smem + PRE);
      sc[tid] = rbf(silu(cs));
      BAR_SYNC(B_F, 256);
      PT(42);
      float acc[8] = {0, 0, 0, 0, 0, 0, 0, 0};
#pragma unroll
      for (int i = 0; i < 8; i++) {
        const float f = sc[i * 32 + (tid >> 3)];
        acc[0] += f * blo(wm[i].x); acc[1] += f * bhi(wm[i].x); acc[2] += f * blo(wm[i].y); acc[3] += f * bhi(wm[i].y);
        acc[4] += f * blo(wm[i].z); acc[5] += f * bhi(wm[i].z); acc[6] += f * blo(wm[i].w); acc[7] += f * bhi(wm[i].w);
      }
#pragma unroll
      for (int i = 0; i < 8; i++) { acc[i] += __shfl_xor_sync(~0u, acc[i], 8); acc[i] += __shfl_xor_sync(~0u, acc[i], 16); }
      float* red = sc + 256;
      if ((tid & 31) < 8) {
#pragma unroll
        for (int i = 0; i < 8; i++) red[(tid >> 5) * 64 + (tid & 7) * 8 + i] = acc[i];
      }
      BAR_SYNC(B_F, 256);
      if (tid < 64) {
        float t = 0;
#pragma unroll
        for (int i = 0; i < 8; i++) t += red[i * 64 + tid];
        asm volatile("st.relaxed.gpu.global.u32 [%0],%1;" ::"l"((unsigned*)g_modp + (b >> 5) * 2048 + (b & 31) * 64 + tid), "r"(U_(t) | 1u) : "memory");
      }
      PH(1); PT(43);
    }
    uint32_t m0[2][4];
#pragma unroll
    for (int i = 0; i < 2; i++)
#pragma unroll
      for (int r = 0; r < 4; r++)
        m0[i][r] = (uint32_t)__bfloat16_as_ushort(mem0[(2 * r) * 1024 + a * 512 + tid * 2 + i]) | ((uint32_t)__bfloat16_as_ushort(mem0[(2 * r + 1) * 1024 + a * 512 + tid * 2 + i]) << 16);
    ROLE_REFRESH
    uint32_t wQ[16][4], wK[16][4], wV[NVR][4];
    uint32_t frag = sb + ((lane & 7) + (lane >> 4) * 8) * 128 + (((iw * 2 + ((lane >> 3) & 1)) ^ (lane & 7)) << 4);
    mbar_wait(wbar, 0);
    PH(2); PT(48);
#pragma unroll
    for (int i = 0; i < 16; i++) { ldsm4t(wQ[i], frag + WO + wg * 32768 + i * 2048); ldsm4t(wK[i], frag + XB + wg * 32768 + i * 2048); }
    FENCE_ASYNC_SMEM();
    PH(3); PT(49);
    CLUSTER_SYNC();
    PT(50);
    auto x_load = [&](int n) {
      asm volatile("{.reg .pred p; elect.sync _|p, 0xffffffff; @p mbarrier.arrive.expect_tx.shared.b64 _,[%2],32768;\n"
                   "@p cp.async.bulk.shared::cluster.global.mbarrier::complete_tx::bytes [%0],[%1],32768,[%2];}"
                   ::"r"(sb + XB), "l"(g_h + n * 4096 + a * 2048), "r"(sb + BARS + 136) : "memory");
    };
    if (wid == 0) {
      wait_h(0);
      PT(47);
      x_load(0);
    }
#define owner ((iw >> 1) == a)
#define oi (wid & 1)
    frag += wg * NVS * 2048;
    {
      const uint32_t rsb = mapa(sb, iw >> 1);
      const uint32_t pp = rsb + PK + (owner ? 0 : 12288) + (oi * 2048 + wg * 1024) + l16;
      const uint32_t mb = sb + MEM + wg * 5120;
      const uint32_t t = sb + TF + wid * TFP + lane * 4;
      sts1(t + T_MEM, mb + lrow);
      sts1(t + T_QK, owner ? L16 + (lane >> 4) * (RK - RQ - 256) + RQ + oi * 1024 + wg * 256 : rsb + RQ + oi * 1024 + 512 + wg * 256 + (l16 >> 2));
      sts1(t + T_O, L16 + OB);
      sts1(t + T_WV, frag);
      sts1(t + T_WO, sb + WO + (wid >> 1) * 16384 + ((lane & 7) + (lane >> 4) * 8) * 128 + ((((wid & 1) * 4 + ((lane >> 3) & 1)) ^ (lane & 7)) << 4));
      sts1(t + T_AR, sb + ARO + wid * 640 + lrow);
      sts1(t + T_PK, pp);
      sts1(t + T_VM, LO(xc) + h * 262144 + (bb * 2 + (iw >> 1)) * XC + X_VM(0) + oi * 2048 + a * 256 + (l16 >> 1));
      sts1(t + T_RX, L16 + RX + iw * 512);
    }
    uint32_t tp = sb + TF + wid * TFP + lane * 4;
    if (!wg) {
      const uint32_t xo = lds1(tp + T_VM);
      stg_b64(mkp(xo, HI(xc)), 0, 0); stg_b64(mkp(xo + X_RING, HI(xc)), 0, 0);
    }
    int wo_ = __shfl_sync(~0u, owner + wg * 2, 0);
    auto park_ptr = [&]() { return lds1(tp + T_PK); };
    auto park = [&](const float* f, int m, int n, uint32_t d) {
      uint32_t w[8];
#pragma unroll
      for (int i = 0; i < 8; i++) w[i] = pk(f[2 * i], f[2 * i + 1]);
      if (wo_ & 1) {
        sts4(d + m * 4096, w[0], w[1], w[2], w[3]); sts4(d + m * 4096 + 512, w[4], w[5], w[6], w[7]);
      } else {
        const uint32_t pb = (d & 0xff000000u) + 1024 + BARS + (m ? 24 + m * 8 : 16);
        {
          sta4(d + m * 4096, w, pb); sta4(d + m * 4096 + 512, w + 4, pb);
        }
      }
    };
    auto xdesc = [&](int n) { return mkdesc(__shfl_sync(~0u, 1024 + XB + wg * 16384, 0), 16, 1024); };
    uint64_t xpre = 0;
    auto rs_issue = [&](float* acc, const uint32_t (&w)[16][4], int n, bool fence, bool pre = false) {
      const uint64_t x = pre ? xpre : xdesc(n);
      if (fence) WG_FENCE();
      wgmma_rs_n32_z(acc, w[0], x);
#pragma unroll
      for (int i = 1; i < 16; i++) wgmma_rs_n32(acc, w[i], x + (i >> 2) * 256 + (i & 3) * 2, 1);
      WG_COMMIT();
    };
    auto v_issue = [&](float* acc, int n, bool fence) {
      const uint64_t dv = mkdesc(__shfl_sync(~0u, 1024 + WVS + wg * NVS * 2048, 0), 16, 1024), x = xdesc(n);
      if (fence) WG_FENCE();
      wgmma_rs_n32_z(acc, wV[0], x);
#pragma unroll
      for (int i = NVR; i < 16; i++) wgmma_ssT_n32(acc, dv + (i - NVR) * 128, x + (i >> 2) * 256 + (i & 3) * 2, 1);
#pragma unroll
      for (int i = 1; i < NVR; i++) wgmma_rs_n32(acc, wV[i], x + (i >> 2) * 256 + (i & 3) * 2, 1);
      WG_COMMIT();
    };
    uint32_t mA;
    auto vk_pass = [&](int n, uint32_t d) {
      float acc[16], acc2[16];
      if (VW) rs_issue(acc, wQ, n, true); else v_issue(acc, n, true);
      rs_issue(acc2, wK, n, false);
      if (n > 0) mbar_wait(sb + BARS + 80, (n - 1) & 1);
      WG_WAIT(1);
      park(acc, 2, n, d);
      mA = lds1(tp + T_MEM);
      BAR_ARRIVE(B_K, 320);
      WG_WAIT(0);
      park(acc2, 1, n, d);
    };
    {
#pragma unroll 1
      for (int n = 0; n < 2; n++) {
        float acc[16];
        asm volatile("" : "+r"(wid), "+r"(wo_));
        mbar_wait(sb + BARS + 136, n);
        PT(51 + n * 3);
        if (n == 1 && wid == 0) {
          asm volatile("{.reg .pred p; elect.sync _|p, 0xffffffff; @p mbarrier.arrive.expect_tx.shared.b64 _,[%0],65536;}" ::"r"(obar) : "memory");
#pragma unroll
          for (int i = 0; i < 4; i++)
            asm volatile("{.reg .pred p; elect.sync _|p, 0xffffffff; @p cp.async.bulk.tensor.2d.shared::cluster.global.mbarrier::complete_tx::bytes [%0],[%1,{%2,%3}],[%4];}"
                         ::"r"(sb + WO + i * 16384), "l"(&mp.wo), "r"(j * 256 + i * 64), "r"(h * 128), "r"(obar) : "memory");
        }
        if (!VW) {
          rs_issue(acc, wQ, n, true);
          if (n > 0) mbar_wait(sb + BARS + 24, 0);
          WG_WAIT(0);
          park(acc, 0, n, park_ptr());
        }
        if (!n) {
          mbar_wait(sb + BARS + 88, 0);
          PT(60);
#pragma unroll
          for (int i = 0; i < NVR; i++) ldsm4t(wV[i], frag + MEM + (wg * (NVR - NVS) + i) * 2048);
          BAR_SYNC(B_H, 256);
#pragma unroll
          for (int i = 0; i < 2; i++) {
            const int k = tid * 2 + i, m = (k >> 3) & 3, r = k & 7;
            sts4(sb + MEM + (k >> 5) * 640 + (r == m ? 512 : m * 128) + r * 16, m0[i][0], m0[i][1], m0[i][2], m0[i][3]);
          }
          if (lane < 8) {
            sts4(sb + ARO + wid * 640 + (lane < 4 ? lane * 144 : 512 + l16), 0x3f803f80, 0x3f803f80, 0x3f803f80, 0x3f803f80);
#pragma unroll
            for (int i = 0; i < 2; i++) sts4(sb + MEM + (wid * 2 + i) * 640 + (lane < 4 ? lane * 144 : 512 + l16), 0x42004200, 0x42004200, 0x42004200, 0x42004200);
          }
        }
        if (VW) {
          v_issue(acc, n, true);
          if (n > 0) mbar_wait(sb + BARS + 24, 0);
          WG_WAIT(0);
          park(acc, 0, n, park_ptr());
        }
        PT(52 + n * 3);
        BAR_ARRIVE(B_C, 320);
        vk_pass(n, park_ptr());
        PT(53 + n * 3);
        if (n > 0) break;
        BAR_ARRIVE(B_X, 320);
        BAR_SYNC(B_H, 256);
        if (wid == 0) x_load(1);
        BAR_SYNC(B_C, 320);
      }
      BAR_ARRIVE(B_P, 384); BAR_ARRIVE(B_X, 320); BAR_ARRIVE(B_Q, 288);
      BAR_SYNC(B_T0, 320);
    }
    PH(4);
    PT(57);
    ROLE_REFRESH
    for (int s = 0; s < 64; s++) {
      asm volatile("" : "+r"(tp), "+r"(wo_));
      wid = wo_ * 2;
      uint32_t vS[NVS][4], bf[8][4], rm;
      if (s > 0) BAR_SYNC(B_R, 320);
#define VMMA(c, w, i) mma16(c, (w)[0], (w)[1], (w)[2], (w)[3], bf[(i) >> 1][((i) & 1) * 2], bf[(i) >> 1][((i) & 1) * 2 + 1])
      {
        float cQ[4] = {0, 0, 0, 0}, cK[4] = {0, 0, 0, 0}, dQ[4] = {0, 0, 0, 0}, dK[4] = {0, 0, 0, 0};
#pragma unroll
        for (int t = 7; t >= 8 - NB1; t--) ldsm4t(bf[t], mA + t * 640);
        SCHED_FENCE(47);
#pragma unroll
        for (int i = 15; i >= 0; i--) {
          if (i & 1) { VMMA(dQ, wQ[i], i); VMMA(dK, wK[i], i); } else { VMMA(cQ, wQ[i], i); VMMA(cK, wK[i], i); }
          if (i == 0) {
#pragma unroll
            for (int e = 0; e < 4; e++) { cQ[e] += dQ[e]; cK[e] += dK[e]; }
          }
          if (i == IB2 && NB2) {
            SCHED_FENCE(49);
#pragma unroll
            for (int t = 7 - NB1; t >= 8 - NB1 - NB2; t--) ldsm4t(bf[t], mA + t * 640);
          }
          if (i == IB3) {
            if (NB1 + NB2 < 8) SCHED_FENCE(51);
#pragma unroll
            for (int t = 7 - NB1 - NB2; t >= 0; t--) ldsm4t(bf[t], mA + t * 640);
            rm = lds1(tp + T_QK); frag = lds1(tp + T_WV);
          }
          if (i == IV) {
#pragma unroll
            for (int u = 0; u < NVP; u++) ldsm4t(vS[NVS - 1 - u], frag + WVS + (NVS - 1 - u) * 2048);
          }
        }
        const uint32_t w0 = pk(cQ[0] * SCS, cQ[1] * SCS), w1 = pk(cQ[2] * SCS, cQ[3] * SCS), w2 = pk(cK[0], cK[1]), w3 = pk(cK[2], cK[3]);
        if (wo_ & 1) {
          stsm4(rm, w0, w1, w2, w3);
          BAR_ARRIVE(B_E, 256);
        } else {
          const uint32_t mm = (rm & 0xff000000u) + 1024 + BARS;
          sta1<0>(rm, w0, mm); sta1<128>(rm, w1, mm);
          sta1<RK - RQ>(rm, w2, mm); sta1<RK - RQ + 128>(rm, w3, mm);
        }
        if (tp - sb - TF < 3 * TFP && tp - sb - TF >= 2 * TFP) TS(0);
      }
      uint32_t oA, woA;
      {
        float cV[4] = {0, 0, 0, 0}, cW[4] = {0, 0, 0, 0};
        static_assert(NVP == 2 && NVR == 5, "schedule");
#define VLD(k) ldsm4t(vS[(k) - NVR], frag + WVS + ((k) - NVR) * 2048)
#define VS_(c, k) VMMA(c, vS[(k) - NVR], k)
        const uint32_t ex = lds1(tp + T_RX), xv = lds1(tp + T_VM);
        VLD(13);
        VS_(cW, 15); VS_(cV, 14); VLD(12); VLD(11); VMMA(cW, wV[4], 4); VMMA(cV, wV[3], 3); VLD(10); VMMA(cW, wV[2], 2); VLD(9);
        VMMA(cV, wV[1], 1); VLD(8); VMMA(cW, wV[0], 0); VLD(7); VS_(cV, 13); VLD(6); VS_(cW, 12); VLD(5);
        VS_(cV, 11); VS_(cW, 10); VS_(cV, 9); VS_(cW, 8); VS_(cV, 7); VS_(cW, 6); VS_(cV, 5);
#pragma unroll
        for (int e = 0; e < 4; e++) cV[e] += cW[e];
        woA = lds1(tp + T_WO);
        oA = lds1(tp + T_O + (s & dZ));
        if (wg) {
          sts4(ex, U_(cV[0]), U_(cV[1]), U_(cV[2]), U_(cV[3]));
          BAR_ARRIVE(B_T2, 256);
        } else {
          BAR_SYNC(B_T2, 256);
          const float4 u = lds4f(ex);
          stg_b64(mkp(xv ^ ((s & 1) * X_RING), HI(xc)), (pk(cV[0] + u.x, cV[1] + u.y) & ~1u) | (((s >> 1) + 1) & 1), pk(cV[2] + u.z, cV[3] + u.w));
        }
      }
      if (s == 63) break;
      {
        mbar_wait(obar, 0);
        const uint32_t woB = woA ^ 32;
        uint32_t wo[16][4];
#pragma unroll
        for (int i = 0; i < NW1; i++) ldsm4t(wo[i], ((i & 1) ? woB : woA) + (i >= WPA ? wo[(i + 16 - WPA) & 15][0] & dZ : 0) + (i >> 1) * 2048);
        xpre = xdesc(0);
        asm volatile("" : "+l"(xpre));
        uint64_t vpre = 0;
        if (VW) { vpre = mkdesc(__shfl_sync(~0u, 1024 + WVS + wg * NVS * 2048, 0), 16, 1024); asm volatile("" : "+l"(vpre)); }
        uint32_t p[4], pm;
        float sum[4] = {0, 0, 0, 0}, su2[4] = {0, 0, 0, 0};
#define PSL() do { ldsm4t(p, oA + (SC - OB)); asm volatile("ldmatrix.sync.aligned.m8n8.x1.trans.shared.b16 {%0},[%1];" : "=r"(pm) : "r"(oA + (SC - OB) + 512) : "memory"); } while (0)
#define PSM() do { const uint32_t one = 0x3f803f80u; mma16(sum, one, one, one, one, p[0], p[1]); mma16(su2, one, one, one, one, p[2], p[3]); mma8(sum, one, one, pm); } while (0)
        BAR_SYNC(B_S, 416);
        if (s < 62) {
          float acc[16];
          if (VW) {
            WG_FENCE();
            wgmma_rs_n32_z(acc, wV[0], xpre);
#pragma unroll
            for (int i = NVR + NH - 1; i > 0 && i > NVR + NH - VO; i--) wgmma_rs_n32(acc, i < NVR ? wV[i] : vS[i - NVR], xpre + (i >> 2) * 256 + (i & 3) * 2, 1);
#pragma unroll
            for (int i = NVR + NH; i < 16; i++) wgmma_ssT_n32(acc, vpre + (i - NVR) * 128, xpre + (i >> 2) * 256 + (i & 3) * 2, 1);
#pragma unroll
            for (int i = NVR + NH - VO; i > 0; i--) wgmma_rs_n32(acc, i < NVR ? wV[i] : vS[i - NVR], xpre + (i >> 2) * 256 + (i & 3) * 2, 1);
            WG_COMMIT();
          } else rs_issue(acc, wQ, s + 2, true, true);
          mbar_wait(sb + BARS + 24, (s + 1) & 1);
          WG_WAIT(0);
#pragma unroll
          for (int i = NW1; i < NWB; i++) ldsm4t(wo[i], ((i & 1) ? woB : woA) + (i >= NW1 + WPC ? wo[(i + 16 - WPC) & 15][0] & dZ : 0) + (i >> 1) * 2048);
          const uint32_t d = park_ptr();
          BAR_SYNC(B_V, 512);
          if (PSO == 1 || PSO == 3) PSL();
          if (PSO == 1) PSM();
          park(acc, 0, s + 2, d);
        } else {
#pragma unroll
          for (int i = NW1; i < NWB; i++) ldsm4t(wo[i], ((i & 1) ? woB : woA) + (i >> 1) * 2048);
          BAR_SYNC(B_V, 512);
          if (PSO == 1 || PSO == 3) PSL();
          if (PSO == 1) PSM();
        }
#pragma unroll
        for (int i = NWB; i < NWP; i++) ldsm4t(wo[i], ((i & 1) ? woB : woA) + (i >> 1) * 2048);
        float inv0, inv1;
        if (!ASM && (PSO == 0 || PSO == 4)) PSL();
        if (!ASM && (PSO == 0 || PSO == 3 || PSO == 4)) PSM();
        if (!ASM && PSO < 2) { inv0 = sum[0] + su2[0]; inv1 = sum[1] + su2[1]; }
        SCHED_FENCE(57);
        BAR_SYNC(B_O, 416);
        float c[2][4] = {{0, 0, 0, 0}, {0, 0, 0, 0}};
        uint32_t o[4][4], arD;
#pragma unroll
        for (int i = 0; i < 2; i++) ldsm4t(o[i], oA + i * 512);
        SCHED_FENCE(46);
        if (PSO > 2) { inv0 = sum[0] + su2[0]; inv1 = sum[1] + su2[1]; }
        if (!ASM && PSO != 2) {
          asm("rcp.approx.ftz.f32 %0,%0;" : "+f"(inv0));
          asm("rcp.approx.ftz.f32 %0,%0;" : "+f"(inv1));
        }
#pragma unroll
        for (int i = 0; i < 16; i++) {
          mma16(c[i & 1], wo[i][0], wo[i][1], wo[i][2], wo[i][3], o[i >> 2][i & 2], o[i >> 2][(i & 2) + 1]);
          if (i == 1) ldsm4t(o[2], oA + 1024);
          if (i == 7) { ldsm4t(o[3], oA + 1536); arD = lds1(tp + T_AR); }
          if (ASM && i == 8) {
            const uint2 u = lds2u((oA & 0xff000030u) / 2 + (oA & 0xff000000u) / 2 + 1024 + BARS + 192);
            asm("rcp.approx.ftz.f32 %0,%1;" : "=f"(inv0) : "f"(F_(u.x)));
            asm("rcp.approx.ftz.f32 %0,%1;" : "=f"(inv1) : "f"(F_(u.y)));
          }
          if (PSO == 2 && i == 8) PSL();
          if (PSO == 2 && i == 12) {
            PSM();
            asm("rcp.approx.ftz.f32 %0,%1;" : "=f"(inv0) : "f"(sum[0] + su2[0]));
            asm("rcp.approx.ftz.f32 %0,%1;" : "=f"(inv1) : "f"(sum[1] + su2[1]));
          }
          if (i + NWP < 16) ldsm4t(wo[(i + NWP) & 15], (((i + NWP) & 1) ? woB : woA) + ((i + NWP) >> 1) * 2048);
        }
        stsm4(arD, pk(c[0][0] * inv0, c[0][1] * inv1), pk(c[0][2] * inv0, c[0][3] * inv1), pk(c[1][0] * inv0, c[1][1] * inv1), pk(c[1][2] * inv0, c[1][3] * inv1));
      }
      const uint32_t d = park_ptr();
      BAR_SYNC(B_W, 384);
      if (s < 62) {
        vk_pass(s + 2, d);
        BAR_ARRIVE(B_P, 384); BAR_ARRIVE(B_X, 320);
        TS(10);
      } else {
        mA = lds1(tp + T_MEM);
      }
    }
  } else if (role == 3) {
    asm volatile("setmaxnreg.dec.sync.aligned.u32 24;");
    if (blockIdx.x >= 128) {
      if (threadIdx.x < 416) {
#pragma unroll 1
        for (int k = 0; k < 32; k++) {
          BAR_SYNC(B_W, 288);
          asm volatile("{.reg .pred p; elect.sync _|p, 0xffffffff; @p cp.async.bulk.tensor.3d.global.shared::cta.bulk_group [%0,{0,%1,%2}],[%3]; cp.async.bulk.commit_group;}"
                       ::"l"(&mp.hst), "r"((blockIdx.x & 1) * 16), "r"(k * 32 + (blockIdx.x & 2) * 8), "r"(sb + 152 * 1024 + (k & 1) * 32768) : "memory");
          if (k < 4 || (k & 3) == 3)
            asm volatile("{.reg .pred p; cp.async.bulk.wait_group 0; elect.sync _|p, 0xffffffff; @p st." HREL ".gpu.global.u32 [%0],%1;}" ::"l"((unsigned*)&g_hprog + (blockIdx.x & 3)), "r"(k + 1) : "memory");
          else BULK_WAIT_READ(0);
        }
        BAR_ARRIVE(B_O, 320);
      } else if (threadIdx.x < 448) {
        wait_h(HPW);
#pragma unroll 1
        for (int r0 = 0; r0 < 1024; r0 += 128) {
          if (r0 == HPR) BAR_ARRIVE(B_O, 320);
          if (threadIdx.x == 416) {
#pragma unroll 1
            for (int r = r0; r < r0 + 128; r += 32) {
#pragma unroll 1
              for (int c = 0; c < 4; c++) {
                tma2d_pf(&mp.wm, 2048 + (blockIdx.x & 3) * 1024 + c * 256, r);
                wait_until(clk(), HPS);
              }
            }
          }
          __syncwarp();
        }
      }
      return;
    }
    ROLE_VARS
    const uint32_t L16 = sb + (tid & 31) * 16;
    CLUSTER_SYNC();
    sts1(sb + PACE + 36, LO(xc) + h * 262144 + X_VM(0));
    auto vm_stage = [&](int s) {
      const uint32_t tag = ((s >> 1) + 1) & 1;
      const char* xm = mkp(lds1(sb + PACE + 36) + (s & 1) * X_RING + iw * XC + (l16 >> 1), HI(xc));
      uint2 m[4];
      CONSUME(LO(xm));
      BAR_SYNC(B_S2, 256);
      if (dZ2 > 1) { const uint32_t c = clk(); while (clk() - c < (uint32_t)dZ2) {} }
      int it = 0;
      while (true) {
#pragma unroll
        for (int i = 0; i < 4; i++) m[i] = ldg_b64(xm + (i >> 1) * 2048 + (i & 1) * 256);
        sts4(L16 + VN + iw * 512, m[0].x, m[0].y, m[1].x, m[1].y);
        sts4(L16 + VN + iw * 512 + 2048, m[2].x, m[2].y, m[3].x, m[3].y);
        if (!anybad(m[0].x, m[1].x, m[2].x, m[3].x, tag)) break;
        RP(2);
        if (++it > SPIN_LIMIT) __trap();
      }
      if (s < 63) BAR_ARRIVE(B_V, 512); else BAR_ARRIVE(B_V, 256);
    };
    if (iw == 0) {
      wait_h(1);
#pragma unroll 1
      for (int s = 0; s < 63; s++) {
        if (s) BAR_SYNC(B_R, 320); else BAR_SYNC(B_Q, 288);
        if (s < 62)
          asm volatile("{.reg .pred p; elect.sync _|p, 0xffffffff; @p mbarrier.arrive.expect_tx.shared.b64 _,[%2],32768;\n"
                       "@p cp.async.bulk.shared::cluster.global.mbarrier::complete_tx::bytes.L2::cache_hint [%0],[%1],32768,[%2],%3;}"
                       ::"r"(sb + XB), "l"(g_h + (s + 2) * 4096 + a * 2048), "r"(sb + BARS + 136), "l"(pol_stream()) : "memory");
        if (s >= 7) {
          const uint32_t zo = b * 160 + l16;
          if (l16 < 160) CONSUME(exch_b128((char*)g_ar + (zo >> 7) * 1024 + (zo & 127) + ((s + 1) & 7) * 128, 0, 0, 0, 0).x);
          __syncwarp();
        }
        if (s < 62) mbar_wait(sb + BARS + 136, s & 1);
        BAR_ARRIVE(B_S, 416);
        vm_stage(s);
        BAR_ARRIVE(B_O, 416);
        BAR_SYNC(B_W, 384);
        FENCE_ASYNC_SMEM();
        asm volatile("{.reg .pred p; elect.sync _|p, 0xffffffff; @p cp.reduce.async.bulk.tensor.2d.global.shared::cta.add.bulk_group [%0,{%1,%2}],[%3];}"
                     ::"l"(&mp.ari), "r"((s & 7) * 64), "r"(j * 40), "r"(sb + ARO) : "memory");
        BULK_COMMIT();
        asm volatile("st.relaxed.gpu.global.u32 [%0],%1;" ::"l"(g_tm + (s & 1) * 128 + b), "r"(gtime()) : "memory");
        TS(3);
        if ((s & 1) && s < 61) wait_h((s + 3) >> 1);
        else if (!(s & 3) && s && b < 2 * GT)
          asm volatile("{.reg .pred p; elect.sync _|p, 0xffffffff; @p red.release.gpu.global.add.u32 [%0],1;}" ::"l"(g_oc + (s - 4) * 8) : "memory");
        BULK_WAIT_READ(0);
      }
      BAR_ARRIVE(B_R, 320);
    } else if (iw == 1) {
      const uint32_t pc = sb + MEM + (lane >> 2) * 640 + (lane & 3) * 144 + (lane & 12), pd = sb + MEM + (lane & 15) * 640 + 576 + (lane & 3) * 16 + (lane & 12);
      uint32_t T = 0, par = 0;
      int est = dA;
      mbar_wait_q(sb + BARS + 88, 0);
      wait_until(clk(), LD3);
#pragma unroll 1
      for (int c = 0; c < 4; c++)
        asm volatile("{.reg .pred p; elect.sync _|p, 0xffffffff; @p cp.async.bulk.prefetch.L2.global [%0], 8192;}" ::"l"((const char*)x + b * 8192 + c * 1048576) : "memory");
#pragma unroll 1
      for (int s = 0; s < 63; s++) {
        if (s) {
          const uint4 tm = ldg_rlx4((const char*)g_tm + ((s + 1) & 1) * 512 + l16);
          const int t0 = tm.x - T, t1 = tm.y - T, t2 = tm.z - T, t3 = tm.w - T;
          const int e = max(dF + (__reduce_add_sync(~0u, (t0 + t1) + (t2 + t3)) >> 7), dV + __reduce_max_sync(~0u, max(max(t0, t1), max(t2, t3))));
          if (s > 1) est += max(min(e >> (e > 0 ? 2 : 1), dP), -dX2);
          T += (s == 1 || e > dM ? e : 0) + est;
        }
        vm_stage(s);
        BAR_SYNC(B_W, 384);
        SCHED_FENCE(70);
        const uint32_t tW = gtime();
        if (s == 0) T = tW + 800;
        const uint32_t te = tW + min(max((int)(T - tW), dD), 2000);
        while ((int)(gtime() - te) < 0) {}
        TS(7);
        int it = 0;
        while (true) {
          ar_fetch(sb + MEM, &mp.ari, s & 7, a, sb + BARS + 112);
          mbar_wait(sb + BARS + 112, par);
          par ^= 1;
          const uint32_t n0 = lds1(pc), n1 = lds1(pc + 5120), n2 = lds1(pd);
          if (!__any_sync(~0u, (tagbad(n0, n1, 0x42004200) | (n2 ^ 0x42004200)) != 0)) break;
          RP(0);
          if (++it > SPIN_LIMIT) __trap();
        }
        BAR_ARRIVE(B_R, 320);
        TS(11);
        if (WPF && s == WPF)
          asm volatile("{.reg .pred p; elect.sync _|p, 0xffffffff; @p cp.async.bulk.prefetch.L2.global [%0], 8192;}" ::"l"((const char*)wo_g + GT * 131072 + b * 8192) : "memory");
      }
    } else {
#define V_LOAD(n) asm volatile("{.reg .pred p; elect.sync _|p, 0xffffffff; @p mbarrier.arrive.expect_tx.shared.b64 _,[%3],8192;\n" \
        "@p cp.async.bulk.tensor.5d.shared::cluster.global.mbarrier::complete_tx::bytes [%0+%4],[%1,{0,0,0,0,%2}],[%3];\n" \
        "@p cp.async.bulk.tensor.5d.shared::cluster.global.mbarrier::complete_tx::bytes [%0+%5],[%1,{0,0,0,1,%2}],[%3];}" \
        ::"r"(sb), "l"(&mp.vx), "r"(h * 32 + X_VRING(n) / 8192), "r"(sb + BARS + 8), "n"(VX0), "n"(VX1) : "memory")
      uint32_t src = L16 + PK + (iw & 1) * 2048;
#define qd (L16 + (lane >> 4) * 256 + QT + (iw & 1) * 1024)
#define vd (LO(xc) + h * 262144 + j * XC + (iw & 1) * 2048 + l16)
#define FINISH [&](int n, int m) { \
_Pragma("unroll") \
        for (int i = 1; i >= 0; i--) { \
          const uint32_t p = src + m * 4096 + i * 512; \
          uint4 u; \
            asm volatile("{.reg .b32 a<4>, b<4>, c<4>, d<4>;\n" \
              "ld.shared.v4.u32 {a0,a1,a2,a3},[%4]; ld.shared.v4.u32 {b0,b1,b2,b3},[%4+1024]; ld.shared.v4.u32 {c0,c1,c2,c3},[%4+12288];\n" \
              "add.rn.bf16x2 a0,a0,b0; add.rn.bf16x2 a1,a1,b1; add.rn.bf16x2 a2,a2,b2; add.rn.bf16x2 a3,a3,b3;\n" \
              "lop3.b32 d0,a0,%5,%4,0xea; ld.shared.v4.u32 {b0,b1,b2,b3},[d0+13312];\n" \
              "add.rn.bf16x2 a0,a0,c0; add.rn.bf16x2 a1,a1,c1; add.rn.bf16x2 a2,a2,c2; add.rn.bf16x2 a3,a3,c3;\n" \
              "add.rn.bf16x2 %0,a0,b0; add.rn.bf16x2 %1,a1,b1; add.rn.bf16x2 %2,a2,b2; add.rn.bf16x2 %3,a3,b3;}" \
              : "=r"(u.x), "=r"(u.y), "=r"(u.z), "=r"(u.w) : "r"(p), "r"(dZ) : "memory"); \
          if (m == (VW ? 0 : 2)) stg_b128(mkp(vd ^ X_VRING(n), HI(xc)) + i * 512, (u.x & ~1u) | X_VTAG(n), u.y, u.z, u.w); \
          else stsm4(qd + (n & 1) * 4096 + (m & 1) * 2048 + i * 256, u.x, u.z, u.y, u.w); \
          SCHED_FENCE(71 + m * 2 + i); \
        } \
      }
#pragma unroll 1
      for (int n = 0; n < 64; n++) {
        src = PIN(src);
        b = __shfl_sync(~0u, lds1(sb + PACE + 24), 0);
        const uint32_t L16 = src - PK - (iw & 1) * 2048;
        auto finish = FINISH;
        if (n < 2) BAR_SYNC(B_C, 320);
        if (n == 1) BAR_ARRIVE(B_T0, 320);
        mbar_wait(sb + BARS + 16, n & 1);
        finish(n, 0);
        __syncwarp();
        if (lane == 0 && n < 63) mbar_arrive_cl(mapa(sb, a ^ 1) + BARS + 24);
        BAR_SYNC(B_K, 320);
        mbar_wait(sb + BARS + 40, n & 1);
        finish(n, 2);
        BAR_SYNC(B_X, 320);
        mbar_wait(sb + BARS + 32, n & 1);
        finish(n, 1);
        BAR_SYNC(B_T, 64);
        if (lane == 0 && n < 63) {
          if (iw == 2) { mbar_expect(sb + BARS + 16, 4096); mbar_expect(sb + BARS + 32, 4096); mbar_expect(sb + BARS + 40, 4096); }
          mbar_arrive_cl(mapa(sb, a ^ 1) + BARS + 80);
        }
        __syncwarp();
        if (n) {
          vm_stage(n - 1);
          BAR_SYNC(B_W, 384);
        } else {
          BAR_SYNC(B_C, 320);
        }
        if (iw == 2) { wait_until(clk(), VDL); V_LOAD(n); }
      }
#undef qd
#undef vd
    }
    vm_stage(63);
  } else {
    asm volatile("setmaxnreg.dec.sync.aligned.u32 %0;" ::"n"(RA_));
    if (blockIdx.x >= 128) return;
    ROLE_VARS
    uint32_t L16 = __shfl_sync(~0u, sb + (tid & 31) * 16, tid & 31);
    CLUSTER_ARRIVE();
    if (tid == 256) {
      const int col = h * 128 + bb * 64;
      for (int c = 0; c < 12 + WIN; c++) {
        const uint32_t mb = sb + PACE + (c % WIN) * 8;
        if (c >= WIN) mbar_wait(mb, (c / WIN - 1) & 1);
        if (c == 7 + WIN) asm volatile("mbarrier.arrive.shared.b64 _,[%0];" ::"r"(wbar) : "memory");
        if (c >= 12) continue;
        if (c == 1) wait_until(clk(), LD1);
        mbar_expect(mb, 16384);
        if (c < 8) tma2d_s(sb + (c & 1) * XB + (c >> 1) * 16384, (c & 1) ? &mp.wk : &mp.wq, col, a * 512 + (c >> 1) * 128, mb);
        else
#pragma unroll 1
          for (int i = (c & 1) * 8; i < (c & 1) * 8 + 8; i++) {
            const int w = (c - 8) >> 1;
            tma2d_s(i < NVR ? sb + MEM + (w * NVR + i) * 2048 : sb + WVS + (w * NVS + i - NVR) * 2048, &mp.wv, col, a * 512 + w * 256 + i * 16, mb);
          }
      }
      asm volatile("mbarrier.arrive.shared.b64 _,[%0];" ::"r"(sb + BARS + 88) : "memory");
      PTT(61, 256);
      wait_until(clk(), LD2);
#pragma unroll 1
      for (int c = 0; c < 4; c++) tma2d_pf(&mp.wo, j * 256 + c * 64, h * 128);
    }
    __syncwarp();
    CLUSTER_WAIT();
#define pr (L16 + SC)
    {
      const int lim = j * 8 + iw * 2 - (lane & 7) - (lane & 8) * 2;
      const bool mk = L16 & 256;
      const int rw = lane >> 2;
      sts4(L16 + TA + iw * 512,
           W3P && iw == 3 ? 0 : iw != 2 ? L16 + KT + (iw & 1) * 256 + (lane >> 4) * 256 : sb + RK + (L16 & 0x80) * 2 + ((L16 >> 1) & 0x80) + (L16 & 0x70),
           L16 + QT + (lane >> 3) * 384, sb + SC + min(lane >> 3, 2) * 256 + (L16 & 0x70) + iw * 4, L16 + (lane >> 4) * 256 + QT + (iw >> 1) * 1024 + (iw & 1) * 256);
      const uint4 u = make_uint4(mk ? 0u : (lim < 0 ? 0xfc00u : 0u) | (lim < -1 ? 0xfc000000u : 0u),
           mk ? 0xfc00fc00u : (lim < 8 ? 0xfc00u : 0u) | (lim < 7 ? 0xfc000000u : 0u),
           ((h * 2 + (iw >> 1)) * 1024 + (j * 8 + rw) * 8 + (((iw & 1) * 4 + ((lane & 3) ^ (rw >> 1))) ^ rw)) * 16, sb + OT + iw * 512 + (L16 & 0x70) * 4 + (((L16 >> 3) ^ (L16 >> 1)) & 0x30));
      if (AT8) { const uint32_t t = sb + TA + 2048 + iw * 512 + lane * 8; sts1(t, u.x); sts1(t + 4, u.y); sts1(t + 256, u.z); sts1(t + 260, u.w); }
      else sts4(L16 + TA + 2048 + iw * 512, u.x, u.y, u.z, u.w);
    }
    {
      const uint32_t xh = LO(xc) + h * 262144, xs = xh + X_SC + iw * 1024 + min(lane, 16 + (lane & 7)) * 8;
      sts4(L16 + TA + 4096 + iw * 512, xh + X_SC + j * 256 + iw * 64 + lpub, xs, dS, iw != 2 ? 0 : U_(SCS));
      sts1(L16 + TA + 12 + iw * 512, xs + X_TOK + j * 4096);
      if (AT8) { const uint32_t t = sb + TA + 6144 + iw * 256 + lane * 8; sts1(t, xs + X_TOK + j * 4096); sts1(t + 4, lds1(L16 + TA + 8 + iw * 512)); }
    }
    uint32_t tA = L16 + TA + iw * 512;
#define tw (tA - L16 != TA + 1024)
#define w3_ (tA - L16 == TA + 1536)
#define XP_(lo) mkp(lo, HI(xc))
    auto publish = [&](char* d, const uint2& w) { stg_b64(d, w.x, w.y); };
    {
      const uint32_t xo = lds1(tA + 4096);
#pragma unroll 1
      for (int i = 0; i < 10; i++) stg_b64(XP_(xo + (i & 1) * X_RING + (i >> 1) * 4096), 0, 0);
    }
    BAR_SYNC(B_P, 384);
    for (int s = 0; s < 64; s++) {
      asm volatile("" : "+r"(L16), "+r"(tA));
      const uint32_t tag = ((s >> 1) + 1) & 1, ring = (s & 1) * X_RING;
      const uint4 t0 = lds4(tA);
      const uint4 tx = lds4(tA + 4096);
      const uint32_t xo = tx.x ^ ring, xs = tx.y ^ ring;
      const float gm = F_(tx.w);
      const uint32_t qA = t0.y + (ring >> 5);
      uint32_t c0;
      uint2 ts[4];
      uint4 v[4];
      uint32_t af[2][4], qt[4][4];
      {
        const uint32_t aA = t0.x + (tw ? ring >> 5 : 0);
        uint32_t ql[2][4], qr[2][4];
        uint2 pw_;
        float c[4] = {0, 0, 0, 0}, d[4] = {0, 0, 0, 0};
        if (s == PDS) asm volatile("griddepcontrol.launch_dependents;");
#pragma unroll
        for (int i = 0; i < 4; i++) ldsm4t_p(qt[i], qA + i * 128, t0.x);
        mbar_wait(sb + BARS + 8, s & 1);
        TS(4);
        BAR_SYNC(B_E, 256);
#define PACK(c) make_uint2(pkh(fmaf(c[2], gm, c[0] * SCS), fmaf(c[3], gm, c[1] * SCS), tag), pkh(c[2] * SCS, c[3] * SCS, tag))
        ldsm4t_p(ql[0], L16 + RQ, t0.x); ldsm4t_p(ql[1], L16 + RQ + 1024, t0.x); ldsm4t_p(af[0], aA, t0.x); ldsm4t_p(af[1], aA + 1024, t0.x);
        CONSUME(xo);
#define QSUM(t, i) addbf(addbf(ql[t][i], ql[t][i + 2]), addbf(qr[t][i], qr[t][i + 2]))
#define STAIL mma16(c, af[0][0], af[0][1], af[0][2], af[0][3], QSUM(0, 0), QSUM(0, 1)); mma16(d, af[1][0], af[1][1], af[1][2], af[1][3], QSUM(1, 0), QSUM(1, 1));
        if (tw) {
          mbar_wait(sb + BARS, s & 1);
          TS(8);
          ldsm4t_p(qr[0], L16 + RQ + 512, t0.x); ldsm4t_p(qr[1], L16 + RQ + 1536, t0.x);
          STAIL
          pw_ = make_uint2(pkh(c[0] + d[0], c[1] + d[1], tag), pkh(c[2] + d[2], c[3] + d[3], tag));
        } else {
          uint32_t ar[2][4];
          mbar_wait(sb + BARS, s & 1);
          ldsm4t(qr[0], L16 + RQ + 512); ldsm4t(qr[1], L16 + RQ + 1536); ldsm4t(ar[0], aA + 512); ldsm4t(ar[1], aA + 1536);
#pragma unroll
          for (int i = 0; i < 8; i++) af[i >> 2][i & 3] = addbf(af[i >> 2][i & 3], ar[i >> 2][i & 3]);
          STAIL
          pw_.x = pw_.y = pkh((c[0] + c[2]) + (d[0] + d[2]), (c[1] + c[3]) + (d[1] + d[3]), tag);
        }
        publish(XP_(xo), pw_);
        c0 = clk() + tx.z;
        TS(1);
      }
      uint2 r[4];
      {
        float e[4][4];
#pragma unroll
        for (int i = 0; i < 4; i++) e[i][0] = e[i][1] = e[i][2] = e[i][3] = 0.f;
        {
#pragma unroll
          for (int i = 0; i < 4; i++) mma16(e[i], af[0][0], af[0][1], af[0][2], af[0][3], qt[i][0], qt[i][1]);
#pragma unroll
          for (int i = 0; i < 4; i++) mma16(e[i], af[1][0], af[1][1], af[1][2], af[1][3], qt[i][2], qt[i][3]);
        }
        SCHED_FENCE(55);
        if (VE) {
          v[0] = lds4(tA + (VX0 - TA)); v[1] = lds4(tA + (VX0 - TA) + 2048); v[2] = lds4(tA + (VX1 - TA)); v[3] = lds4(tA + (VX1 - TA) + 2048);
          if (VE == 2) CONSUME(v[0].x & v[1].x & v[2].x & v[3].x);
        }
        if (s < 63) BAR_ARRIVE(B_S, 416);
        SCHED_FENCE(58);
        if (!VE) { v[0] = lds4(tA + (VX0 - TA)); v[1] = lds4(tA + (VX0 - TA) + 2048); v[2] = lds4(tA + (VX1 - TA)); v[3] = lds4(tA + (VX1 - TA) + 2048); }
#pragma unroll
        for (int i = 0; i < 4; i++) ts[i] = PACK(e[i]);
        while ((int)(clk() - c0) < 0) {}
        TS(5);
#pragma unroll
        for (int u = 0; u < 4; u++) r[u] = ldg_b64(XP_(xs) + u * 256);
        BAR_ARRIVE(B_S2, 256);
      }
      const uint32_t fn = (L16 & 256) ? 0xfc00fc00u : 0u;
      float4 e = softmax2<false>(r, 0, fn);
      const bool vbad = anybad(v[0].x, v[1].x, v[2].x, v[3].x, X_VTAG(s));
      if (BADS(r)) {
        int it = 0;
        if (s > 8) sts1(tA + 4096 + 8, min(lds1(tA + 4096 + 8) + dX, 500));
        do {
          RP(1);
          if (++it > SPIN_LIMIT) __trap();
#pragma unroll
          for (int u = 0; u < 4; u++) r[u] = ldg_b64(XP_(xs) + u * 256);
        } while (BADS(r));
        e = softmax2<false>(r, 0, fn);
      }
      sts1(t0.z, pk(e.x, e.y)); sts1(t0.z + 128, pk(e.z, e.w));
#pragma unroll
      for (int i = 0; i < 4; i++) publish(XP_(xo) + X_TOK + i * 4096, ts[i]);
      TS(6);
      if (s < 63) BAR_SYNC(B_V, 512); else BAR_SYNC(B_V, 256);
      uint32_t O[4];
      uint4 vn[2];
      {
        uint32_t p[4], pm;
        ldsm4t(p, pr);
        vn[0] = lds4(tA + (VN - TA)); vn[1] = lds4(tA + (VN - TA) + 2048);
        asm volatile("ldmatrix.sync.aligned.m8n8.x1.trans.shared.b16 {%0},[%1];" : "=r"(pm) : "r"(pr + 512) : "memory");
        pv_mem(p, pm, v, vn, O, sb + BARS + 192 + ((L16 >> 1) & 24), L16);
        if (vbad) {
          int it = 0;
          do {
            if (++it > SPIN_LIMIT) __trap();
#pragma unroll
            for (int u = 0; u < 4; u++) v[u] = ldg_b128(XP_((LO(xc) + (lds1(sb + PACE + 24) >> 2) * 262144 + ((tA - L16 - TA) >> 9) * XC + l16) ^ X_VRING(s)) + X_VX(u));
          } while (anybad(v[0].x, v[1].x, v[2].x, v[3].x, X_VTAG(s)));
          pv_mem(p, pm, v, vn, O, sb + BARS + 192 + ((L16 >> 1) & 24), L16);
        }
      }
      stsm4(tA + (OB - TA), O[0], O[1], O[2], O[3]);
      if (s < 63) BAR_ARRIVE(B_O, 416);
      TS(2);
      c0 = clk() + (LG && s == 63 ? 0 : dG);
      SCHED_FENCE(60);
      if (tA == sb + TA) mbar_expect(sb + BARS, 2048);
      const uint32_t vs[4] = {addbf(vn[0].x, vn[0].z), addbf(vn[0].y, vn[0].w), addbf(vn[1].x, vn[1].z), addbf(vn[1].y, vn[1].w)};
      {
        const uint2 t3 = AT8 ? lds2u(sb + TA + 6144 + ((tA - sb - TA) >> 1)) : make_uint2(lds1(tA + 12), lds1(tA + 8));
        const char* xt = XP_(t3.x ^ ring);
        const uint2 t1 = lds2u(AT8 ? tA - (l16 >> 1) + 2048 : tA + 2048);
        const uint32_t pw = t3.y;
        uint2 rt[4];
        CONSUME(LO(xt) ^ t1.x ^ pw);
        while ((int)(clk() - c0) < 0) {}
        int it = 0;
        do {
          if (++it > SPIN_LIMIT) __trap();
#pragma unroll
          for (int u = 0; u < 4; u++) rt[u] = ldg_b64(xt + u * 256);
        } while (BADS(rt));
        const float4 et = softmax2<true>(rt, t1.x, t1.y);
        sts1(pw + SCT, pk(et.x, et.y)); sts1(pw + SCT + 128, pk(et.z, et.w));
      }
      s = PIN(s);
      BAR_SYNC(B_SC, 128);
      {
        uint32_t Ot[4], p[4], pm;
        const uint2 t2 = lds2u(AT8 ? tA - (l16 >> 1) + 2048 + 256 : tA + 2048 + 8);
        ldsm4t(p, pr + SCT);
        asm volatile("ldmatrix.sync.aligned.m8n8.x1.trans.shared.b16 {%0},[%1];" : "=r"(pm) : "r"(pr + SCT + 512) : "memory");
        char* od = (char*)g_O + ((s >> 2) * 1048576 + (s & 3) * 4096) + t2.x;
        CONSUME(LO(od) ^ HI(od) ^ pm ^ p[3]);
        TS(9);
        if (s < 62) BAR_SYNC(B_P, 384);
        pv_tok(p, pm, v, vs, Ot);
        asm volatile("stmatrix.sync.aligned.m8n8.x4.trans.shared.b16 [%0],{%1,%2,%3,%4};" ::"r"(t2.y), "r"(Ot[0]), "r"(Ot[1]), "r"(Ot[2]), "r"(Ot[3]) : "memory");
        __syncwarp();
        *(uint4*)od = lds4(tA + (OT - TA));
      }
    }
  }
  PH(5);
  if (threadIdx.x == 0) FT(40);
  PDUMP();
}
#undef wg
#undef iw
#undef h
#undef j
#undef a
#undef bb
#undef oi
#undef owner
#undef pr
#undef PIN
#undef XP_
#undef tw
#undef w3_
#undef lane
#undef l16
#undef lrow
#undef lpub

namespace ffn {
constexpr uint32_t STG = 196608;
constexpr uint32_t PRM = 229376;
constexpr uint32_t BARS = PRM + 2176;
constexpr uint32_t SMEM = BARS + 16 * 8;
}
#define UBASE (g_O + rb * 65536)
struct FfnMaps { CUtensorMap wo, w1a, w1b, w2, xp, out, x, xps, wo4; int zero[16]; };

template <int N>
__device__ __forceinline__ void wg_ss(float* d, uint64_t a, uint64_t b, int sd) {
  if (N == 128) wgmma_ss_n128(d, a, b, sd);
  if (N == 192) wgmma_ss_n192(d, a, b, sd);
  if (N == 256) wgmma_ss_n256(d, a, b, sd);
}
template <int N>
__device__ __forceinline__ void ffn_issue(float* acc, uint32_t full, uint32_t par, uint32_t a, uint32_t b, bool first) {
  mbar_wait(full, par);
  const uint64_t da = mkdesc(0, 0, 1024) | a, db = mkdesc(0, 0, 1024) | b;
  WG_FENCE();
#pragma unroll
  for (int j = 0; j < 4; j++) wg_ss<N>(acc, da + j * 2, db + j * 128, !first || j);
  WG_COMMIT();
}
__device__ __forceinline__ void ffn_release(uint32_t leader, uint32_t e) {
  asm volatile("{.reg .pred p; setp.ne.u32 p,%0,0; @p mbarrier.arrive.shared.b64 _,[%1];}" ::"r"(leader), "r"(e) : "memory");
}
__device__ __forceinline__ void ffn_done(unsigned* cnt) {
  asm volatile("{.reg .pred p; cp.async.bulk.wait_group 0; elect.sync _|p, 0xffffffff; @p red.relaxed.gpu.global.add.u32 [%0],1;}" ::"l"(cnt) : "memory");
}
template <int N>
__device__ __forceinline__ void acc_fence(float* d) {
#pragma unroll
  for (int i = 0; i < N; i++) asm volatile("" : "+f"(d[i])::"memory");
}
__device__ __forceinline__ float gelu_h(float hx) {
  float t;
  asm("tanh.approx.f32 %0,%1;" : "=f"(t) : "f"(hx * fmaf(hx * hx, 8 * 0.0356774081f, 2 * 0.7978845608f)));
  return fmaf(hx, t, hx);
}
template <int N>
__device__ __forceinline__ void ffn_gelu(uint32_t (&u)[N], int i, const uint2& b, uint32_t stw, uint32_t z) {
  uint32_t o[4];
#pragma unroll
  for (int e = 0; e < 4; e++) {
    uint32_t h;
    asm("fma.rn.bf16x2 %0,%1,%2,%3;" : "=r"(h) : "r"(u[i * 4 + e]), "r"(0x3f003f00), "r"(e < 2 ? b.x : b.y));
    o[e] = pk(gelu_h(blo(h)), gelu_h(bhi(h)));
#pragma unroll
    for (int j = i * 4 + e; j < N - 16; j += 16) u[j] = u[j + 16] ^ z;
  }
  stsm4(stw ^ (i * 32), o[0], o[1], o[2], o[3]);
}
__device__ __forceinline__ void ffn_store(uint32_t stg, const uint4* dst) {
  FENCE_ASYNC_SMEM();
  __syncwarp();
  asm volatile("{.reg .pred p; elect.sync _|p, 0xffffffff; @p cp.async.bulk.global.shared::cta.bulk_group [%0],[%1],2048; cp.async.bulk.commit_group;\n"
               "cp.async.bulk.wait_group.read 1;}" ::"l"(dst), "r"(stg) : "memory");
  __syncwarp();
}
__device__ __forceinline__ uint32_t halfbf(uint32_t v) { return pk(0.5f * blo(v), 0.5f * bhi(v)); }

__device__ __forceinline__ void ffn_spare(const FfnMaps& mp, uint32_t sb, int cb, const char* x) {
  using namespace ffn;
  const int tid = threadIdx.x, lane = tid & 31, wid = __shfl_sync(~0u, tid >> 5, 0);
  const uint32_t full = sb + BARS, emp = full + 48, xbar = full + 104, XA = 147456;
  if (tid < 128) sts1(sb + PRM + (tid >> 4) * 64 + (tid & 3) * 16 + ((tid >> 2) & 3) * 4, pk(__ldcg(g_mod + 2048 + cb * 256 + tid * 2), __ldcg(g_mod + 2048 + cb * 256 + tid * 2 + 1)));
  __syncthreads();
  if (wid == 8) {
    int st = 0; uint32_t ph = 1;
#pragma unroll 1
    for (int rb = 0; rb < 16; rb++) {
#pragma unroll 1
      for (int i = rb ? 16 : 0; i < (rb < 15 ? 32 : 16); i++)
        asm volatile("prefetch.global.L2 [%0];" ::"l"(x + (rb * 128 + i * 8 + (lane >> 2)) * 2048 + cb * 512 + (lane & 3) * 128) : "memory");
      if (rb < 15) {
        int it = 0;
        while (ld_acq(g_oc + rb * 32) < 2 * GT) { __nanosleep(500); if (++it > SPIN_LIMIT) __trap(); }
      } else asm volatile("griddepcontrol.wait;" ::: "memory");
      FENCE_ASYNC_G();
#pragma unroll 1
      for (int k = 0; k < GT; k++) {
        mbar_wait_q(emp + st * 8, ph);
        e_expect_tma3d(sb + st * 49152 + 16384, &mp.wo4, k * 64, cb * 4, full + st * 8, 49152);
        e_bulk_ld(sb + st * 49152, g_O + rb * 65536 + k * 1024, 16384, full + st * 8);
        if (++st == 3) { st = 0; ph ^= 1; }
      }
    }
  } else if (wid < 8) {
    const int wg = wid >> 2, row0 = wid * 16;
    const uint32_t stg = sb + row0 * 128, stw = stg + (lane & 15) * 128 + (((lane >> 4) ^ (lane & 7)) << 4), prm = sb + PRM + (lane & 3) * 16;
    const uint32_t aw = (uint32_t)mkdesc(1024 + wg * 8192, 16, 0), leader = (tid & 127) == 0;
    constexpr uint32_t bw = (1024 + 16384) / 16 + (8192 / 16 << 16);
    int st = 0, prev = 0; uint32_t ph = 0;
#pragma unroll 1
    for (int rb = 0; rb < 16; rb++) {
      float acc[128];
      if (tid == 0) FT(44 + rb);
#pragma unroll 1
      for (int k = 0; k < GT; k++) {
        ffn_issue<256>(acc, full + st * 8, ph, aw + st * 3072, bw + st * 3072, k == 0);
        if (k == 2) {
          if (rb) ffn_done(g_oc + 480 + rb * 32 + cb);
          BAR_SYNC(1, 256);
          if (tid == 0) {
            mbar_expect(xbar, 65536);
            for (int i = 0; i < 4; i++) tma2d(sb + (i & 2 ? STG : XA) + (i & 1) * 16384, &mp.x, cb * 256 + i * 64, rb * 128, xbar);
          }
          __syncwarp();
        }
        WG_WAIT(1);
        ffn_release(leader && k, emp + prev * 8);
        prev = st;
        if (++st == 3) { st = 0; ph ^= 1; }
      }
      WG_WAIT(0);
      ffn_release(leader, emp + prev * 8);
      acc_fence<128>(acc);
      mbar_wait(xbar, rb & 1);
      uint4 pa, pn = lds4(prm);
      uint32_t xn[2][4];
#define XAD(j) ((stw ^ (((j) & 3) * 32)) + ((j) & 8 ? STG : XA) + ((j) & 4) * 4096)
      ldsm4(xn[0], XAD(0)); ldsm4(xn[1], XAD(1));
#pragma unroll
      for (int j = 0; j < 16; j++) {
        const uint32_t a = XAD(j), xv[4] = {xn[j & 1][0], xn[j & 1][1], xn[j & 1][2], xn[j & 1][3]};
        uint32_t o[4];
        if (j < 14) ldsm4(xn[j & 1], XAD(j + 2));
        if (!(j & 1)) { pa = pn; if (j < 14) pn = lds4(prm + ((j >> 1) + 1) * 64); }
#pragma unroll
        for (int e = 0; e < 4; e++) {
          const uint32_t g = (j & 1) ? (e < 2 ? pa.z : pa.w) : (e < 2 ? pa.x : pa.y);
          o[e] = pk(fmaf(blo(g), acc[j * 8 + e * 2], blo(xv[e])), fmaf(bhi(g), acc[j * 8 + e * 2 + 1], bhi(xv[e])));
        }
        stsm4(a, o[0], o[1], o[2], o[3]);
      }
      FENCE_ASYNC_SMEM();
      __syncwarp();
#pragma unroll 1
      for (int i = 0; i < 4; i++)
        asm volatile("{.reg .pred p; elect.sync _|p, 0xffffffff; @p cp.async.bulk.tensor.2d.global.shared::cta.bulk_group [%0,{%1,%2}],[%3];}"
                     ::"l"(&mp.xps), "r"(cb * 256 + i * 64), "r"(rb * 128 + row0), "r"(stg + (i & 2 ? STG : XA) + (i & 1) * 16384) : "memory");
      BULK_COMMIT();
    }
    ffn_done(g_oc + 512 + 15 * 32 + cb);
  }
  __syncthreads();
}

#define SL(st) (GT % 6 == 0 ? (st) : (st) + GT % 6 - ((st) >= 6 - GT % 6 ? 6 : 0))
__global__ void __launch_bounds__(384, 1)
k_ffn(const __grid_constant__ FfnMaps mp, const bf16* __restrict__ b1, const bf16* __restrict__ b2, const char* x) {
  using namespace ffn;
  extern __shared__ __align__(1024) char smem[];
  const uint32_t sb = (uint32_t)__cvta_generic_to_shared(smem);
  if ((sb & 0x3FFFF) != 1024) __trap();
  const int tid = threadIdx.x, lane = tid & 31, wg = __shfl_sync(~0u, tid >> 7, 0);
  int tile = ((int)blockIdx.x + 128) % 132;
  uint4 hs = ldg_rlx4(g_hsm);
  if (TMP && tid == 256) asm volatile("prefetch.tensormap [%0];" ::"l"(&mp.wo) : "memory");
  const uint32_t full = sb + BARS, emp = full + 48, xbar = full + 96, rdy = full + 96;
  if (tid == 256) {
#pragma unroll
    for (int i = 0; i < 6; i++) mbar_init(full + i * 8, 1);
    FENCE_ASYNC_SMEM();
  } else if (tid == 288) {
#pragma unroll
    for (int i = 0; i < 6; i++) mbar_init(emp + i * 8, 2);
  } else if (tid == 320) {
    mbar_init(xbar, 2);
#pragma unroll
    for (int i = 1; i < 4; i++) mbar_init(rdy + i * 8, 1);
    FENCE_ASYNC_SMEM();
  }
  __syncthreads();
  {
    uint32_t sm, nsm;
    asm volatile("mov.u32 %0,%%smid; mov.u32 %1,%%nsmid;" : "=r"(sm), "=r"(nsm));
    const uint32_t t = sm >> 1, u = ((t - 32) * 37) >> 8;
    const uint32_t g = t < 32 ? t & 7 : t < 60 ? t - 31 - u * 7 : 0, i = (t < 32 ? t >> 3 : t < 60 ? 4 + u : t - 58) * 2 + (sm & 1);
    const uint32_t m = ((g >> 1) * 4 + (i & 3)) * 8 + (g & 1) * 4 + (i >> 2);
    const bool usual = ((hs.x & hs.y & hs.z & hs.w) >> 2) == 30 && ((hs.x | hs.y | hs.z | hs.w) >> 2) == 30;
    if (nsm == 132)
      tile = sm == hs.x ? 128 : sm == hs.y ? 129 : sm == hs.z ? 130 : sm == hs.w ? 131 : usual ? m : sm - (hs.x < sm) - (hs.y < sm) - (hs.z < sm) - (hs.w < sm);
    tile = __shfl_sync(~0u, tile, 0);
  }
  if (tile >= 128) {
    ffn_spare(mp, sb, tile & 3, x);
    if (tid == 0) wait_cnt(&g_fcnt, 128);
    return;
  }
  const int rb = tile >> 3, nb = tile & 7;
  if (tid == 256) FT(34);
  const int wid = __shfl_sync(~0u, tid >> 5, 0);
  if (wid == 8) {
#pragma unroll
    for (int k = 0; k < 6; k++) { if (k) wait_until(clk(), 200); e_expect_tma3d<true>(sb + SL(k) * 32768 + 16384, &mp.wo, (GT + k) * 64, nb * 2, full + k * 8, 32768); }
    if (lane == 0) FT(36);
  } else if (wid == 9) {
    asm volatile("griddepcontrol.wait;" ::: "memory");
    if (lane == 0) FT(35);
    FENCE_ASYNC_G();
#pragma unroll
    for (int k = 0; k < 6; k++) { if (k) wait_until(clk(), 200); e_bulk_ld<true>(sb + SL(k) * 32768, g_O + rb * 65536 + (GT + k) * 1024, 16384, full + k * 8); }
    if (lane == 0) FT(2);
  } else if (tid == 320) {
    asm volatile("red.relaxed.gpu.global.add.u32 [%0],1;" ::"l"(&g_fcnt) : "memory");
  }
  unsigned* cnt = g_cnt + rb * 128;
  if (wg == 2) {
    asm volatile("setmaxnreg.dec.sync.aligned.u32 40;");
    const int pw = __shfl_sync(~0u, (tid >> 5) & 3, 0);
    uint32_t me = emp, mp_ = 0, st = 0;
    auto wait1 = [&]() { mbar_wait_q(me, mp_); me += 8; if (me == emp + 48) { me = emp; mp_ ^= 1; } };
#define NEXTS() do { if (++st == 6) st = 0; } while (0)
#define KT2(k) ((k) < 2 ? nb * 2 + (k) : (k) >= 16 ? (k) - 16 : (k) - 2 < nb * 2 ? (k) - 2 : (k))
#define KT3(k) (((k) & 7) * 7 + ((k) >> 3))
    if (pw == 0) {
#pragma unroll 1
      for (int k = GT + 6; k < 64; k++) {
        wait1();
        e_expect_tma3d<true>(sb + SL(st) * 32768 + 16384, &mp.wo, k * 64, nb * 2, full + st * 8, 32768);
        NEXTS();
      }
      wait1(); wait1(); wait1();
#pragma unroll 1
      for (int k = 0; k < 32; k++) {
        const int kt = KT2(k);
        if (k != 3) wait1();
        e_expect_tma3d<true>(sb + (k & 3) * 49152 + 16384, k < 16 ? &mp.w1a : &mp.w1b, kt * 64, nb * 7 + (k >> 4) * 4, full + st * 8, k < 2 ? 32768 : k < 16 ? 49152 : 40960);
        NEXTS();
      }
#pragma unroll 1
      for (int k = 0; k < 56; k++) {
        if (k != 2 && k != 5) wait1();
        e_expect_tma3d<true>(sb + SL(st) * 32768 + 16384, &mp.w2, KT3(k) * 64, nb * 2, full + st * 8, 32768);
        NEXTS();
      }
    } else if (pw == 1) {
      const uint4* A = g_O + rb * 65536;
#pragma unroll 1
      for (int k = GT + 6; k < 64; k++) {
        wait1();
        e_bulk_ld<true>(sb + SL(st) * 32768, A + k * 1024, 16384, full + st * 8);
        NEXTS();
      }
#pragma unroll 1
      for (int k = 0; k < 6; k++) wait1();
      wait_cnt(cnt, 64);
      if (lane == 0) FT(29);
      FENCE_ASYNC_G();
      st = (66 - GT) % 6;
      A = g_h2 + rb * 16384;
#pragma unroll 1
      for (int k = 2; k < 32; k++) {
        const int kt = KT2(k);
        if (k > 3) wait1();
        if (k == 3) wait_until(clk(), 250);
        e_bulk_ld(sb + (k & 3) * 49152, A + kt * 1024, 16384, full + st * 8);
        NEXTS();
      }
      A = UBASE;
#pragma unroll 1
      for (int k = 0; k < 56; k++) {
        if ((k & 15) == 0 && k < 48) { mbar_wait_q(rdy + 8 + (k >> 1), 0); FENCE_ASYNC_G(); }
        if (k != 2 && k != 5) wait1();
        e_bulk_ld<true>(sb + SL(st) * 32768, A + KT3(k) * 1024, 16384, full + st * 8);
        NEXTS();
      }
    } else if (pw == 2) {
      asm volatile("griddepcontrol.wait;" ::: "memory");
      if (lane < 16) g_modp[tile * 16 + lane] = make_uint4(0, 0, 0, 0);
      if (lane == 16 && tile == 0) g_hprog = make_uint4(0, 0, 0, 0);
      __nanosleep(2000);
      if (lane < 5) asm volatile("prefetch.tensormap [%0];" ::"l"(&mp.w1a + lane) : "memory");
      int it = 0;
      while (ld_acq(g_oc + 512 + rb * 32 + (nb >> 1)) < 8) { __nanosleep(200); if (++it > SPIN_LIMIT) __trap(); }
      FENCE_ASYNC_G();
#pragma unroll
      for (int i = 0; i < 8; i++) asm volatile("prefetch.global.L2 [%0];" ::"l"((const char*)g_xp + (rb * 128 + i * 16 + (lane >> 1)) * 2048 + nb * 256 + (lane & 1) * 128) : "memory");
      if (!it) __nanosleep(1500);
      if (lane == 0) {
        mbar_expect(xbar, 32768);
        tma2d(sb + STG, &mp.xp, nb * 128, rb * 128, xbar);
        tma2d(sb + STG + 16384, &mp.xp, nb * 128 + 64, rb * 128, xbar);
      }
    } else {
      const uint32_t prm = sb + PRM;
      const uint2 v2 = ((const uint2*)(b2 + nb * 128))[lane];
      auto put = [&](uint32_t at, uint32_t u, uint32_t v) {
        const uint32_t a = prm + at + (lane >> 3) * 64 + (lane & 1) * 32 + ((lane >> 1) & 3) * 4;
        sts1(a, u); sts1(a + 16, v);
      };
      put(1024, v2.x, v2.y);
#pragma unroll
      for (int i = 0; i < 7; i++) sts1(prm + 1280 + i * 128 + (lane & 3) * 32 + (lane >> 2) * 4, halfbf(((const uint32_t*)(b1 + nb * 448))[i * 32 + lane]));
      const float4* md = (const float4*)(g_mod + nb * 128) + lane;
      const float4 ga = __ldcg(md + 512), sbv = __ldcg(md + 768), cb = __ldcg(md + 1024), gb = __ldcg(md + 1280);
      put(0, pk(ga.x, ga.y), pk(ga.z, ga.w));
      put(256, pk(1.f + cb.x, 1.f + cb.y), pk(1.f + cb.z, 1.f + cb.w));
      put(512, pk(sbv.x, sbv.y), pk(sbv.z, sbv.w));
      put(768, pk(gb.x, gb.y), pk(gb.z, gb.w));
      __syncwarp();
      if (lane == 0) {
        asm volatile("mbarrier.arrive.shared.b64 _,[%0];" ::"r"(xbar) : "memory");
#pragma unroll 1
        for (int i = 1; i < 4; i++) {
          int it = 0;
          while (ld_acq(cnt + i * 32) < 64) { __nanosleep(200); if (++it > SPIN_LIMIT) __trap(); }
          asm volatile("mbarrier.arrive.shared.b64 _,[%0];" ::"r"(rdy + i * 8) : "memory");
        }
      }
    }
  } else {
    const int w = __shfl_sync(~0u, (tid >> 5) & 3, 0), q = lane & 3;
    const uint32_t leader = (tid & 127) == 0;
    const uint32_t prm = sb + PRM + q * 16;
#define PRM2(v, a, b, at) if (!(j & 1)) v = lds4(prm + (at) + (j >> 1) * 64); const uint32_t a = (j & 1) ? v.z : v.x, b = (j & 1) ? v.w : v.y;
    const int row0 = wg * 64 + w * 16;
    const uint32_t stg = sb + STG + row0 * 128;
    const uint32_t stw = stg + (lane & 15) * 128 + (((lane >> 4) ^ (lane & 7)) << 4);
    const uint32_t aw = (uint32_t)mkdesc(1024 + wg * 8192, 16, 0);
    constexpr uint32_t bw = (1024 + 16384) / 16 + (8192 / 16 << 16);
    uint32_t x1[32];
    {
      float acc[64];
      int st = 0, prev = 0; uint32_t ph = 0;
#pragma unroll 1
      for (int k = 0; k < 64 - GT; k++) {
        ffn_issue<128>(acc, full + st * 8, ph, aw + SL(st) * 2048, bw + SL(st) * 2048, k == 0);
        if (tid == 0 && (k & 7) == 0) FT(3 + (k >> 3));
        if (tid == 0 && k > 0 && k < 8) FT(19 + k);
        WG_WAIT(1);
        ffn_release(leader && k, emp + prev * 8);
        prev = st;
        if (++st == 6) { st = 0; ph ^= 1; }
      }
      WG_WAIT(0);
      ffn_release(leader, emp + prev * 8);
      acc_fence<64>(acc);
      asm volatile("setmaxnreg.inc.sync.aligned.u32 232;");
      PH(7); if (tid == 0) { FT(11); FC(38); }
      mbar_wait(xbar, 0);
      float s0 = 0, s1 = 0, q0 = 0, q1 = 0;
      uint4 pa;
#pragma unroll
      for (int j = 0; j < 8; j++) {
        uint32_t xv[4];
        ldsm4(xv, (stw ^ ((j & 3) * 32)) + (j >> 2) * 16384);
        PRM2(pa, g0, g1, 0)
        float* d = acc + j * 8;
#pragma unroll
        for (int e = 0; e < 4; e++) {
          const uint32_t g = e < 2 ? g0 : g1;
          x1[j * 4 + e] = pk(fmaf(blo(g), d[e * 2], blo(xv[e])), fmaf(bhi(g), d[e * 2 + 1], bhi(xv[e])));
          d[e * 2] = blo(x1[j * 4 + e]); d[e * 2 + 1] = bhi(x1[j * 4 + e]);
        }
        s0 += (d[0] + d[1]) + (d[4] + d[5]);
        s1 += (d[2] + d[3]) + (d[6] + d[7]);
      }
      s0 += __shfl_xor_sync(~0u, s0, 1); s1 += __shfl_xor_sync(~0u, s1, 1);
      s0 += __shfl_xor_sync(~0u, s0, 2); s1 += __shfl_xor_sync(~0u, s1, 2);
      s0 *= 1.f / 128; s1 *= 1.f / 128;
#pragma unroll
      for (int j = 0; j < 16; j++) {
        float* d = acc + j * 4;
        d[0] -= s0; d[1] -= s0; d[2] -= s1; d[3] -= s1;
        q0 += d[0] * d[0] + d[1] * d[1]; q1 += d[2] * d[2] + d[3] * d[3];
      }
      q0 += __shfl_xor_sync(~0u, q0, 1); q1 += __shfl_xor_sync(~0u, q1, 1);
      q0 += __shfl_xor_sync(~0u, q0, 2); q1 += __shfl_xor_sync(~0u, q1, 2);
      uint4* sp = g_stat + (rb * 128 + row0) * 4 + (lane >> 2);
      if (q == 0) stg_b128(sp + nb * 8, U_(s0), min(U_(q0), 0xfffffffeu), U_(s1), U_(q1));
      if (tid == 0) FT(12);
#pragma unroll
      for (int j = 0; j < 8; j++) {
        PRM2(pa, c0, c1, 256)
        float* d = acc + j * 8;
        d[0] *= blo(c0); d[1] *= bhi(c0); d[2] *= blo(c0); d[3] *= bhi(c0);
        d[4] *= blo(c1); d[5] *= bhi(c1); d[6] *= blo(c1); d[7] *= bhi(c1);
      }
      acc_fence<64>(acc);
      uint4 r0, r1;
      int it = 0;
      while (true) {
        r0 = ldg_b128(sp + q * 16); r1 = ldg_b128(sp + q * 16 + 8);
        if (__all_sync(~0u, r0.y != ~0u && r1.y != ~0u)) break;
        if (++it > SPIN_LIMIT) __trap();
      }
      if (tid == 0) FT(13);
      float m0 = F_(r0.x) + F_(r1.x), m1 = F_(r0.z) + F_(r1.z);
      m0 += __shfl_xor_sync(~0u, m0, 1); m1 += __shfl_xor_sync(~0u, m1, 1);
      m0 += __shfl_xor_sync(~0u, m0, 2); m1 += __shfl_xor_sync(~0u, m1, 2);
      m0 *= 0.125f; m1 *= 0.125f;
      float a = F_(r0.x) - m0, b = F_(r1.x) - m0, c = F_(r0.z) - m1, d = F_(r1.z) - m1;
      float v0 = F_(r0.y) + F_(r1.y) + 128.f * (a * a + b * b);
      float v1 = F_(r0.w) + F_(r1.w) + 128.f * (c * c + d * d);
      v0 += __shfl_xor_sync(~0u, v0, 1); v1 += __shfl_xor_sync(~0u, v1, 1);
      v0 += __shfl_xor_sync(~0u, v0, 2); v1 += __shfl_xor_sync(~0u, v1, 2);
      const float rs0 = rsqrtf(v0 * (1.f / 1024) + 1e-5f), rs1 = rsqrtf(v1 * (1.f / 1024) + 1e-5f);
      const float k0 = (s0 - m0) * rs0, k1 = (s1 - m1) * rs1;
      uint4 pc[4], ph_[4];
#pragma unroll
      for (int j = 0; j < 8; j++) {
        if (j == 0) {
#pragma unroll
          for (int i = 0; i < 4; i++) { pc[i] = lds4(prm + 256 + i * 64); ph_[i] = lds4(prm + 512 + i * 64); }
        }
        const uint32_t c0 = (j & 1) ? pc[j >> 1].z : pc[j >> 1].x, c1 = (j & 1) ? pc[j >> 1].w : pc[j >> 1].y;
        const uint32_t h0 = (j & 1) ? ph_[j >> 1].z : ph_[j >> 1].x, h1 = (j & 1) ? ph_[j >> 1].w : ph_[j >> 1].y;
        const float* d = acc + j * 8;
        stsm4((stw ^ ((j & 3) * 32)) + (j >> 2) * 16384,
              pk(fmaf(d[0], rs0, fmaf(k0, blo(c0), blo(h0))), fmaf(d[1], rs0, fmaf(k0, bhi(c0), bhi(h0)))),
              pk(fmaf(d[2], rs1, fmaf(k1, blo(c0), blo(h0))), fmaf(d[3], rs1, fmaf(k1, bhi(c0), bhi(h0)))),
              pk(fmaf(d[4], rs0, fmaf(k0, blo(c1), blo(h1))), fmaf(d[5], rs0, fmaf(k0, bhi(c1), bhi(h1)))),
              pk(fmaf(d[6], rs1, fmaf(k1, blo(c1), blo(h1))), fmaf(d[7], rs1, fmaf(k1, bhi(c1), bhi(h1)))));
      }
      FENCE_ASYNC_SMEM();
      __syncwarp();
      asm volatile("{.reg .pred p; elect.sync _|p, 0xffffffff; @p cp.async.bulk.global.shared::cta.bulk_group [%0],[%1],2048;\n"
                   "@p cp.async.bulk.global.shared::cta.bulk_group [%0+16384],[%1+16384],2048; cp.async.bulk.commit_group;}"
                   ::"l"(g_h2 + (size_t)(rb * 16 + nb * 2) * 1024 + row0 * 8), "r"(stg) : "memory");
      if (wg) BAR_SYNC(2, 128); else BAR_SYNC(3, 128);
    }
    PH(8); if (tid == 0) FT(14);
    const uint4* dst = UBASE + nb * 7 * 1024 + row0 * 8;
    int st = (64 - GT) % 6, prev = 0, flip = 0; uint32_t ph = (64 - GT) / 6 & 1, bs = sb + PRM + 1280 + q * 32;
#define NEXT() do { prev = st; if (++st == 6) { st = 0; ph ^= 1; } } while (0)
#define QUAD(N, acc, u, t, off, first) \
_Pragma("unroll") \
      for (int i = 0; i < 4; i++) { \
        const uint2 b = lds2u(bs + i * 8); \
        ffn_issue<N>(acc, full + st * 8, ph, aw + (off), bw + (off), i == 0 && (first)); \
        if (i == 0 && (t)) { ffn_store(stg + flip, dst); flip ^= 16384; dst += 1024; } \
        if (i == 3 && ((t) == 2 || (t) == 4)) ffn_done(cnt + (t) * 16); \
        WG_WAIT(1); \
        ffn_release(leader, emp + prev * 8); \
        NEXT(); \
        ffn_gelu(u, i, b, stw + flip, mp.zero[0]); \
      } \
      bs += 128;
    uint32_t u0[64], u1[48];
    {
      float acc[128];
#pragma unroll 1
      for (int k = 0; k < 16; k++) {
        ffn_issue<256>(acc, full + st * 8, ph, aw + (k < 2 ? STG / 16 + k * 1024 : (k & 3) * 3072), bw + (k & 3) * 3072, k == 0);
        if (tid == 0 && (k & 7) == 0) FT(15 + (k >> 3));
        if (k == 0) { ffn_done(cnt); if (tid == 0) FT(32); }
        if (FTS_ != 2 && tid == 0 && k && k < 5) FT(59 + k);
        WG_WAIT(1);
        ffn_release(leader && k, emp + prev * 8);
        NEXT();
      }
      WG_WAIT(0);
      acc_fence<128>(acc);
#pragma unroll
      for (int i = 0; i < 64; i++) u0[i] = pk(acc[2 * i], acc[2 * i + 1]);
    }
    PH(9); if (tid == 0) FT(17);
    {
      float acc[96];
#pragma unroll 1
      for (int t = 0; t < 4; t++) {
        if (FTS_ != 2 && tid == 0) FT(42 + t);
        QUAD(192, acc, u0, t, i * 3072, t == 0)
      }
      WG_WAIT(0);
      acc_fence<96>(acc);
#pragma unroll
      for (int i = 0; i < 48; i++) u1[i] = pk(acc[2 * i], acc[2 * i + 1]);
    }
    {
      float acc[64];
#pragma unroll 1
      for (int t = 4; t < 7; t++) {
        if (FTS_ != 2 && tid == 0) FT(42 + t);
        QUAD(128, acc, u1, t, SL(st) * 2048, t == 4)
      }
      uint4 pg[4], pb[4];
#pragma unroll
      for (int i = 0; i < 4; i++) { pg[i] = lds4(prm + 768 + i * 64); pb[i] = lds4(prm + 1024 + i * 64); }
#pragma unroll 1
      for (int k = 12; k < 56; k++) {
        if (FTS_ != 2 && tid == 0 && (k & 3) == 0) FT(46 + (k >> 2));
        ffn_issue<128>(acc, full + st * 8, ph, aw + SL(st) * 2048, bw + SL(st) * 2048, false);
        if (k == 12) ffn_store(stg + flip, dst);
        if (k == 16) ffn_done(cnt + 96);
        WG_WAIT(1);
        ffn_release(leader, emp + prev * 8);
        NEXT();
      }
      WG_WAIT(0);
      acc_fence<64>(acc);
      PH(13); if (tid == 0) { FT(30); FC(39); }
#pragma unroll
      for (int j = 0; j < 8; j++) {
        const uint32_t g0 = (j & 1) ? pg[j >> 1].z : pg[j >> 1].x, g1 = (j & 1) ? pg[j >> 1].w : pg[j >> 1].y;
        const uint32_t h0 = (j & 1) ? pb[j >> 1].z : pb[j >> 1].x, h1 = (j & 1) ? pb[j >> 1].w : pb[j >> 1].y;
        const float* d = acc + j * 8;
        const uint32_t* xv = x1 + j * 4;
        stsm4((stw ^ ((j & 3) * 32)) + (j >> 2) * 16384,
              pk(blo(xv[0]) + blo(g0) * (d[0] + blo(h0)), bhi(xv[0]) + bhi(g0) * (d[1] + bhi(h0))),
              pk(blo(xv[1]) + blo(g0) * (d[2] + blo(h0)), bhi(xv[1]) + bhi(g0) * (d[3] + bhi(h0))),
              pk(blo(xv[2]) + blo(g1) * (d[4] + blo(h1)), bhi(xv[2]) + bhi(g1) * (d[5] + bhi(h1))),
              pk(blo(xv[3]) + blo(g1) * (d[6] + blo(h1)), bhi(xv[3]) + bhi(g1) * (d[7] + bhi(h1))));
        if ((j & 3) == 3) {
          FENCE_ASYNC_SMEM();
          __syncwarp();
          asm volatile("{.reg .pred p; elect.sync _|p, 0xffffffff; @p cp.async.bulk.tensor.2d.global.shared::cta.bulk_group [%0,{%1,%2}],[%3];}"
                       ::"l"(&mp.out), "r"(nb * 128 + (j >> 2) * 64), "r"(rb * 128 + row0), "r"(stg + (j >> 2) * 16384) : "memory");
          if (j == 3) { SCHED_FENCE(47); acc_fence<32>(acc + 32); }
        }
      }
      BULK_COMMIT(); BULK_WAIT_READ(0);
    }
    PH(14); if (tid == 0) FT(31);
  }
}

typedef CUresult (*EncFn)(CUtensorMap*, CUtensorMapDataType, cuuint32_t, void*, const cuuint64_t*, const cuuint64_t*, const cuuint32_t*,
                          const cuuint32_t*, CUtensorMapInterleave, CUtensorMapSwizzle, CUtensorMapL2promotion, CUtensorMapFloatOOBfill);
static void map2d(EncFn enc, CUtensorMap* m, const void* p, int rows, int cols, int boxRows) {
  cuuint64_t d[2] = {(cuuint64_t)cols, (cuuint64_t)rows}, s[1] = {(cuuint64_t)cols * 2};
  cuuint32_t b[2] = {64, (cuuint32_t)boxRows}, e[2] = {1, 1};
  enc(m, CU_TENSOR_MAP_DATA_TYPE_BFLOAT16, 2, (void*)p, d, s, b, e, CU_TENSOR_MAP_INTERLEAVE_NONE, CU_TENSOR_MAP_SWIZZLE_128B,
      CU_TENSOR_MAP_L2_PROMOTION_L2_128B, CU_TENSOR_MAP_FLOAT_OOB_FILL_NONE);
}
static void map3d(EncFn enc, CUtensorMap* m, const void* p, int rows, int cols, int nch) {
  cuuint64_t d[3] = {64, (cuuint64_t)rows, (cuuint64_t)(cols / 64)}, s[2] = {(cuuint64_t)cols * 2, 128};
  cuuint32_t b[3] = {64, 64, (cuuint32_t)nch}, e[3] = {1, 1, 1};
  enc(m, CU_TENSOR_MAP_DATA_TYPE_BFLOAT16, 3, (void*)p, d, s, b, e, CU_TENSOR_MAP_INTERLEAVE_NONE, CU_TENSOR_MAP_SWIZZLE_128B,
      CU_TENSOR_MAP_L2_PROMOTION_L2_128B, CU_TENSOR_MAP_FLOAT_OOB_FILL_NONE);
}

extern "C" void kernel_launch(void* const* d_in, const int* in_sizes, int n_in, void* d_out, int out_size) {
  const bf16* x = (const bf16*)d_in[0];
  const bf16* mem0 = (const bf16*)d_in[1];
  void* fn = nullptr;
  cudaDriverEntryPointQueryResult qr;
  cudaGetDriverEntryPoint("cuTensorMapEncodeTiled", &fn, cudaEnableDefault, &qr);
  EncFn enc = (EncFn)fn;
  FfnMaps fm = {};
  map3d(enc, &fm.wo, d_in[5], 4096, 1024, 2);
  map3d(enc, &fm.w1a, d_in[8], 1024, 3584, 4);
  map3d(enc, &fm.w1b, d_in[8], 1024, 3584, 3);
  map3d(enc, &fm.w2, d_in[10], 3584, 1024, 2);
  map2d(enc, &fm.x, x, 2048, 1024, 128);
  map2d(enc, &fm.out, d_out, 2048, 1024, 16);
  map3d(enc, &fm.wo4, d_in[5], 4096, 1024, 4);
  {
    void* xp = nullptr;
    cudaGetSymbolAddress(&xp, g_xp);
    map2d(enc, &fm.xp, xp, 2048, 1024, 128);
    map2d(enc, &fm.xps, xp, 2048, 1024, 16);
  }
  RecMaps rm = {};
  map2d(enc, &rm.wq, d_in[2], 1024, 4096, 128);
  map2d(enc, &rm.wk, d_in[3], 1024, 4096, 128);
  map2d(enc, &rm.wv, d_in[4], 1024, 4096, 16);
  map2d(enc, &rm.wo, d_in[5], 4096, 1024, 128);
  map3d(enc, &rm.wm3, d_in[13], 1024, 6144, 8);
  {
    cuuint64_t d[2] = {6144, 1024}, sd[1] = {12288};
    cuuint32_t bi[2] = {256, 32}, e[2] = {1, 1};
    enc(&rm.wm, CU_TENSOR_MAP_DATA_TYPE_BFLOAT16, 2, d_in[13], d, sd, bi, e, CU_TENSOR_MAP_INTERLEAVE_NONE, CU_TENSOR_MAP_SWIZZLE_NONE,
        CU_TENSOR_MAP_L2_PROMOTION_NONE, CU_TENSOR_MAP_FLOAT_OOB_FILL_NONE);
  }
  {
    void* hp = nullptr;
    cudaGetSymbolAddress(&hp, g_h);
    cuuint64_t d[3] = {64, 32, 1024}, sd[2] = {128, 4096};
    cuuint32_t bi[3] = {64, 16, 16}, e[3] = {1, 1, 1};
    enc(&rm.hst, CU_TENSOR_MAP_DATA_TYPE_BFLOAT16, 3, hp, d, sd, bi, e, CU_TENSOR_MAP_INTERLEAVE_NONE, CU_TENSOR_MAP_SWIZZLE_NONE,
        CU_TENSOR_MAP_L2_PROMOTION_NONE, CU_TENSOR_MAP_FLOAT_OOB_FILL_NONE);
  }
  {
    void* ar = nullptr;
    cudaGetSymbolAddress(&ar, g_ar);
    cuuint64_t d[2] = {512, 160}, sd[1] = {1024};
    cuuint32_t bi[2] = {64, 40}, e[2] = {1, 1};
    enc(&rm.ari, CU_TENSOR_MAP_DATA_TYPE_BFLOAT16, 2, ar, d, sd, bi, e, CU_TENSOR_MAP_INTERLEAVE_NONE, CU_TENSOR_MAP_SWIZZLE_NONE,
        CU_TENSOR_MAP_L2_PROMOTION_NONE, CU_TENSOR_MAP_FLOAT_OOB_FILL_NONE);
  }
  cudaFuncSetAttribute(k_ffn, cudaFuncAttributeMaxDynamicSharedMemorySize, ffn::SMEM);
  cudaFuncSetAttribute(k_rec, cudaFuncAttributeMaxDynamicSharedMemorySize, rec::SMEM);
  char* xc = nullptr;
  cudaGetSymbolAddress((void**)&xc, g_xc);
  xc += (0 - (uintptr_t)xc) & 0x3FFFF;
  {
    cuuint64_t d[5] = {256, 4, 2, 2, 1024}, sd[4] = {rec::XC, 512, 2048, 8192};
    cuuint32_t bi[5] = {256, 4, 2, 1, 1}, e[5] = {1, 1, 1, 1, 1};
    enc(&rm.vx, CU_TENSOR_MAP_DATA_TYPE_BFLOAT16, 5, xc, d, sd, bi, e, CU_TENSOR_MAP_INTERLEAVE_NONE, CU_TENSOR_MAP_SWIZZLE_NONE,
        CU_TENSOR_MAP_L2_PROMOTION_NONE, CU_TENSOR_MAP_FLOAT_OOB_FILL_NONE);
  }
  cudaStream_t st = cudaStreamPerThread;
  int dF = 450, dA = 2700, dS = 300, dM = 120, dG = 350, dP = 24, dX = 48, dD = 350, dZ = 0, dZ2 = 1, dV = 370, dX2 = 60;
  k_rec<<<132, 512, rec::SMEM, st>>>(rm, mem0, x, (const bf16*)d_in[12], (const bf16*)d_in[13], (const bf16*)d_in[5], xc, dF, dA, dS, dM, dG, dP, dX, dD, dZ, dZ2, dV, dX2);
  cudaLaunchConfig_t cfg = {};
  cfg.gridDim = dim3(132); cfg.blockDim = dim3(384); cfg.dynamicSmemBytes = ffn::SMEM; cfg.stream = st;
  cudaLaunchAttribute at[1];
  at[0].id = cudaLaunchAttributeProgrammaticStreamSerialization;
  at[0].val.programmaticStreamSerializationAllowed = 1;
  cfg.attrs = at; cfg.numAttrs = 1;
  cudaLaunchKernelEx(&cfg, k_ffn, fm, (const bf16*)d_in[9], (const bf16*)d_in[11], (const char*)x);
}
```

```cpp
#include <cuda_runtime.h>
#include <cuda.h>
#include <cuda_bf16.h>
#include <stdint.h>

typedef __nv_bfloat16 bf16;

__device__ __align__(16) float g_mod[6144];
__device__ __align__(1024) uint4 g_modp[4 * 512];
__device__ __align__(128) uint4 g_hsm[8];
__device__ __align__(128) unsigned g_fcnt_[32];
__device__ __align__(128) uint4 g_hprog_[8];
#define g_fcnt g_fcnt_[0]
#define g_hprog g_hprog_[0]
__device__ __align__(1024) uint4 g_h[2048 * 1024 / 8];
__device__ __align__(1024) uint4 g_O[2048 * 4096 / 8];
__device__ __align__(1024) uint4 g_h2[2048 * 1024 / 8];
__device__ __align__(1024) uint4 g_xp[2048 * 1024 / 8];
__device__ __align__(1024) unsigned g_oc[2 * 16 * 32];
__device__ __align__(1024) uint4 g_stat[2048 * 4];
__device__ __align__(1024) unsigned g_cnt[16 * 4 * 32];
__device__ __align__(1024) uint4 g_ar[160 * 64];
__device__ __align__(1024) uint4 g_xc[33 * 16384];
__device__ __align__(1024) unsigned g_tm[128 * 8];
#define PH(i)
#define FT(i)
#define PT(i)
#define PTT(i, t)
#define PDUMP()
#define PZERO()
#define FC(i)
#define RP(i)
#define RPN(i, s)
#define TSV(i, v)
#define TS(i)

#define FTS_ 0
#define NB1 2
#define NB2 3
#define IB2 14
#define IB3 11
#define IV 3
#define LD1 1000
#define LD2 800
#define LD3 8000
#define VDL 100
#define GT 12
#define HPS 400
#define HPR 512
#define HPW 2
#define PDS 2
#define VW 1
#define NH 4
#define NWA 2
#define NWB 7
#define VO 5
#define VE 1
#define WPC 3
#define WPA 4
#define LG 1
#define NCS 1
#define PSO 0
#define NWQ 10
#define ASM 1
#define W3P 0
#define AT8 1
#define X1 1
#define XD1 400
#define TMP 1
#define WPF 0
#define HREL "relaxed"
constexpr int WIN = 2, RF_ = 208, RA_ = 488 - 2 * RF_;
#define SPIN_LIMIT (1 << 20)
__device__ __forceinline__ uint64_t mkdesc(uint32_t addr, uint32_t lbo, uint32_t sbo) {
  return (uint64_t)((addr & 0x3FFFF) >> 4) | ((uint64_t)(lbo >> 4) << 16) | ((uint64_t)(sbo >> 4) << 32) | (1ull << 62);
}
__device__ __forceinline__ void mbar_init(uint32_t a, int c) { asm volatile("mbarrier.init.shared.b64 [%0],%1;" ::"r"(a), "r"(c) : "memory"); }
__device__ __forceinline__ void mbar_wait(uint32_t a, uint32_t par) {
  asm volatile(
      "{.reg .pred p; .reg .u32 n;\n"
      "mov.u32 n, 0;\n"
      "W: mbarrier.try_wait.parity.shared.b64 p,[%0],%1;\n"
      "@p bra D;\n"
      "add.u32 n, n, 1;\n"
      "setp.lt.u32 p, n, %2;\n"
      "@p bra W;\n"
      "trap;\n"
      "D:}" ::"r"(a), "r"(par), "n"(SPIN_LIMIT) : "memory");
}
__device__ __forceinline__ void mbar_wait_q(uint32_t a, uint32_t par) {
  asm volatile(
      "{.reg .pred p; .reg .u32 n;\n"
      "mov.u32 n, 0;\n"
      "W: mbarrier.try_wait.parity.shared.b64 p,[%0],%1,4000;\n"
      "@p bra D;\n"
      "add.u32 n, n, 1;\n"
      "setp.lt.u32 p, n, %2;\n"
      "@p bra W;\n"
      "trap;\n"
      "D:}" ::"r"(a), "r"(par), "n"(SPIN_LIMIT / 16) : "memory");
}
__device__ __forceinline__ void mbar_expect(uint32_t a, uint32_t b) { asm volatile("mbarrier.arrive.expect_tx.shared.b64 _,[%0],%1;" ::"r"(a), "r"(b) : "memory"); }
__device__ __forceinline__ uint32_t mapa(uint32_t a, uint32_t cta) { uint32_t r; asm("mapa.shared::cluster.u32 %0,%1,%2;" : "=r"(r) : "r"(a), "r"(cta)); return r; }
__device__ __forceinline__ void mbar_arrive_cl(uint32_t a) { asm volatile("mbarrier.arrive.shared::cluster.b64 _,[%0];" ::"r"(a) : "memory"); }
__device__ __forceinline__ void tma2d(uint32_t dst, const CUtensorMap* m, int c0, int c1, uint32_t mb) {
  asm volatile("cp.async.bulk.tensor.2d.shared::cluster.global.mbarrier::complete_tx::bytes [%0],[%1,{%2,%3}],[%4];" ::"r"(dst), "l"(m), "r"(c0), "r"(c1), "r"(mb) : "memory");
}
__device__ __forceinline__ uint64_t pol_stream() { uint64_t p; asm("createpolicy.fractional.L2::evict_first.b64 %0, 1.0;" : "=l"(p)); return p; }
__device__ __forceinline__ void tma2d_s(uint32_t dst, const CUtensorMap* m, int c0, int c1, uint32_t mb) {
  asm volatile("cp.async.bulk.tensor.2d.shared::cluster.global.mbarrier::complete_tx::bytes.L2::cache_hint [%0],[%1,{%2,%3}],[%4],%5;" ::"r"(dst), "l"(m), "r"(c0), "r"(c1), "r"(mb), "l"(pol_stream()) : "memory");
}
__device__ __forceinline__ void tma2d_pf(const CUtensorMap* m, int c0, int c1) {
  asm volatile("cp.async.bulk.prefetch.tensor.2d.L2.global [%0,{%1,%2}];" ::"l"(m), "r"(c0), "r"(c1) : "memory");
}
template <bool STREAM = false>
__device__ __forceinline__ void e_expect_tma3d(uint32_t dst, const CUtensorMap* m, int c1, int c2, uint32_t mb, uint32_t bytes) {
  if (STREAM) asm volatile("{.reg .pred p; elect.sync _|p, 0xffffffff; @p mbarrier.arrive.expect_tx.shared.b64 _,[%4],%5;\n"
               "@p cp.async.bulk.tensor.3d.shared::cluster.global.mbarrier::complete_tx::bytes.L2::cache_hint [%0],[%1,{0,%2,%3}],[%4],%6;}" ::"r"(dst), "l"(m), "r"(c1), "r"(c2), "r"(mb), "r"(bytes), "l"(pol_stream()) : "memory");
  else asm volatile("{.reg .pred p; elect.sync _|p, 0xffffffff; @p mbarrier.arrive.expect_tx.shared.b64 _,[%4],%5;\n"
               "@p cp.async.bulk.tensor.3d.shared::cluster.global.mbarrier::complete_tx::bytes [%0],[%1,{0,%2,%3}],[%4];}" ::"r"(dst), "l"(m), "r"(c1), "r"(c2), "r"(mb), "r"(bytes) : "memory");
}
template <bool STREAM = false>
__device__ __forceinline__ void e_bulk_ld(uint32_t dst, const void* src, uint32_t n, uint32_t mb) {
  if (STREAM) asm volatile("{.reg .pred p; elect.sync _|p, 0xffffffff; @p cp.async.bulk.shared::cluster.global.mbarrier::complete_tx::bytes.L2::cache_hint [%0],[%1],%2,[%3],%4;}" ::"r"(dst), "l"(src), "r"(n), "r"(mb), "l"(pol_stream()) : "memory");
  else asm volatile("{.reg .pred p; elect.sync _|p, 0xffffffff; @p cp.async.bulk.shared::cluster.global.mbarrier::complete_tx::bytes [%0],[%1],%2,[%3];}" ::"r"(dst), "l"(src), "r"(n), "r"(mb) : "memory");
}
#define BULK_COMMIT() asm volatile("cp.async.bulk.commit_group;" ::: "memory")
#define BULK_WAIT_READ(n) asm volatile("cp.async.bulk.wait_group.read " #n ";" ::: "memory")
#define FENCE_ASYNC_SMEM() asm volatile("fence.proxy.async.shared::cta;" ::: "memory")
#define FENCE_ASYNC_G() asm volatile("fence.proxy.async.global;" ::: "memory")
#define WG_FENCE() asm volatile("wgmma.fence.sync.aligned;" ::: "memory")
#define WG_COMMIT() asm volatile("wgmma.commit_group.sync.aligned;" ::: "memory")
#define WG_WAIT(n) asm volatile("wgmma.wait_group.sync.aligned " #n ";" ::: "memory")
#define BAR_SYNC(id, n) asm volatile("bar.sync %0,%1;" ::"n"(id), "n"(n) : "memory")
#define BAR_ARRIVE(id, n) asm volatile("bar.arrive %0,%1;" ::"n"(id), "n"(n) : "memory")
#define SCHED_FENCE(k) asm volatile("{.reg .pred p; setp.ne.u32 p,%0,0; @p trap;}" ::"r"(mp.zero[(k) - 46]) : "memory")
#define CLUSTER_ARRIVE() asm volatile("fence.release.sync_restrict::shared::cta.cluster; barrier.cluster.arrive.relaxed.aligned;" ::: "memory")
#define CLUSTER_WAIT() asm volatile("barrier.cluster.wait.aligned;" ::: "memory")
#define CLUSTER_SYNC() do { CLUSTER_ARRIVE(); CLUSTER_WAIT(); } while (0)
__device__ __forceinline__ uint32_t pk(float lo, float hi) { uint32_t r; asm("cvt.rn.bf16x2.f32 %0,%1,%2;" : "=r"(r) : "f"(hi), "f"(lo)); return r; }
__device__ __forceinline__ float blo(uint32_t v) { return __uint_as_float(v << 16); }
__device__ __forceinline__ float bhi(uint32_t v) { return __uint_as_float(v & 0xffff0000u); }
__device__ __forceinline__ void ldsm4(uint32_t* r, uint32_t a) {
  asm volatile("ldmatrix.sync.aligned.m8n8.x4.shared.b16 {%0,%1,%2,%3},[%4];" : "=r"(r[0]), "=r"(r[1]), "=r"(r[2]), "=r"(r[3]) : "r"(a) : "memory");
}
__device__ __forceinline__ void ldsm4t(uint32_t* r, uint32_t a) {
  asm volatile("ldmatrix.sync.aligned.m8n8.x4.trans.shared.b16 {%0,%1,%2,%3},[%4];" : "=r"(r[0]), "=r"(r[1]), "=r"(r[2]), "=r"(r[3]) : "r"(a) : "memory");
}
__device__ __forceinline__ void ldsm4t_p(uint32_t* r, uint32_t a, uint32_t on) {
  if (!W3P) { ldsm4t(r, a); return; }
  asm volatile("{.reg .pred p; setp.ne.u32 p,%5,0; mov.b32 %0,%4; mov.b32 %1,%4; mov.b32 %2,%4; mov.b32 %3,%4; @p ldmatrix.sync.aligned.m8n8.x4.trans.shared.b16 {%0,%1,%2,%3},[%4];}" : "=&r"(r[0]), "=&r"(r[1]), "=&r"(r[2]), "=&r"(r[3]) : "r"(a), "r"(on) : "memory");
}
__device__ __forceinline__ void stsm4(uint32_t a, uint32_t r0, uint32_t r1, uint32_t r2, uint32_t r3) {
  asm volatile("stmatrix.sync.aligned.m8n8.x4.shared.b16 [%0],{%1,%2,%3,%4};" ::"r"(a), "r"(r0), "r"(r1), "r"(r2), "r"(r3) : "memory");
}
__device__ __forceinline__ void mma16(float* d, uint32_t a0, uint32_t a1, uint32_t a2, uint32_t a3, uint32_t b0, uint32_t b1) {
  asm volatile("mma.sync.aligned.m16n8k16.row.col.f32.bf16.bf16.f32 {%0,%1,%2,%3},{%4,%5,%6,%7},{%8,%9},{%0,%1,%2,%3};"
               : "+f"(d[0]), "+f"(d[1]), "+f"(d[2]), "+f"(d[3]) : "r"(a0), "r"(a1), "r"(a2), "r"(a3), "r"(b0), "r"(b1));
}
__device__ __forceinline__ void mma8(float* d, uint32_t a0, uint32_t a1, uint32_t b0) {
  asm volatile("mma.sync.aligned.m16n8k8.row.col.f32.bf16.bf16.f32 {%0,%1,%2,%3},{%4,%5},{%6},{%0,%1,%2,%3};"
               : "+f"(d[0]), "+f"(d[1]), "+f"(d[2]), "+f"(d[3]) : "r"(a0), "r"(a1), "r"(b0));
}
__device__ __forceinline__ float4 lds4f(uint32_t a) { float4 v; asm volatile("ld.shared.v4.f32 {%0,%1,%2,%3},[%4];" : "=f"(v.x), "=f"(v.y), "=f"(v.z), "=f"(v.w) : "r"(a) : "memory"); return v; }
__device__ __forceinline__ uint4 lds4(uint32_t a) { uint4 v; asm volatile("ld.shared.v4.u32 {%0,%1,%2,%3},[%4];" : "=r"(v.x), "=r"(v.y), "=r"(v.z), "=r"(v.w) : "r"(a) : "memory"); return v; }
__device__ __forceinline__ uint2 lds2u(uint32_t a) { uint2 v; asm volatile("ld.shared.v2.u32 {%0,%1},[%2];" : "=r"(v.x), "=r"(v.y) : "r"(a) : "memory"); return v; }
__device__ __forceinline__ uint32_t lds1(uint32_t a) { uint32_t v; asm volatile("ld.shared.u32 %0,[%1];" : "=r"(v) : "r"(a) : "memory"); return v; }
__device__ __forceinline__ void sts4(uint32_t a, uint32_t x, uint32_t y, uint32_t z, uint32_t w) { asm volatile("st.shared.v4.u32 [%0],{%1,%2,%3,%4};" ::"r"(a), "r"(x), "r"(y), "r"(z), "r"(w) : "memory"); }
__device__ __forceinline__ void sts1(uint32_t a, uint32_t x) { asm volatile("st.shared.u32 [%0],%1;" ::"r"(a), "r"(x) : "memory"); }
__device__ __forceinline__ void sta4(uint32_t a, const uint32_t* v, uint32_t mb) {
  asm volatile("st.async.shared::cluster.mbarrier::complete_tx::bytes.v4.b32 [%0],{%1,%2,%3,%4},[%5];" ::"r"(a), "r"(v[0]), "r"(v[1]), "r"(v[2]), "r"(v[3]), "r"(mb) : "memory");
}
__device__ __forceinline__ uint4 ldg_rlx4(const void* p) { uint4 v; asm volatile("ld.relaxed.gpu.global.v4.u32 {%0,%1,%2,%3},[%4];" : "=r"(v.x), "=r"(v.y), "=r"(v.z), "=r"(v.w) : "l"(p) : "memory"); return v; }
__device__ __forceinline__ uint4 ldg_b128(const void* p) {
  uint4 v;
  asm volatile("{.reg .b128 t; .reg .b64 a,b; ld.relaxed.gpu.global.b128 t,[%4]; mov.b128 {a,b},t; mov.b64 {%0,%1},a; mov.b64 {%2,%3},b;}" : "=r"(v.x), "=r"(v.y), "=r"(v.z), "=r"(v.w) : "l"(p) : "memory");
  return v;
}
__device__ __forceinline__ void stg_b128(void* p, uint32_t x, uint32_t y, uint32_t z, uint32_t w) {
  asm volatile("{.reg .b128 t; .reg .b64 a,b; mov.b64 a,{%1,%2}; mov.b64 b,{%3,%4}; mov.b128 t,{a,b}; st.relaxed.gpu.global.b128 [%0],t;}" ::"l"(p), "r"(x), "r"(y), "r"(z), "r"(w) : "memory");
}
__device__ __forceinline__ unsigned ld_acq(const unsigned* p) { unsigned v; asm volatile("ld.acquire.gpu.global.u32 %0,[%1];" : "=r"(v) : "l"(p) : "memory"); return v; }
__device__ __forceinline__ void wait_cnt(const unsigned* p, unsigned n) { int it = 0; while (ld_acq(p) < n) { if (++it > SPIN_LIMIT) __trap(); } }
__device__ __forceinline__ void wait_h(unsigned n) {
  int it = 0;
  while (true) {
    uint4 v;
    asm volatile("{.reg .b128 t; .reg .b64 a,b; ld.acquire.gpu.global.b128 t,[%4]; mov.b128 {a,b},t; mov.b64 {%0,%1},a; mov.b64 {%2,%3},b;}" : "=r"(v.x), "=r"(v.y), "=r"(v.z), "=r"(v.w) : "l"(&g_hprog) : "memory");
    if (min(min(v.x, v.y), min(v.z, v.w)) > n) break;
    if (++it > SPIN_LIMIT) __trap();
    __nanosleep(200);
  }
  FENCE_ASYNC_G();
}
__device__ __forceinline__ uint32_t clk() { uint32_t c; asm volatile("mov.u32 %0,%%clock;" : "=r"(c)); return c; }
__device__ __forceinline__ uint32_t gtime() { uint32_t c; asm volatile("mov.u32 %0,%%globaltimer_lo;" : "=r"(c)); return c; }
__device__ __forceinline__ void wait_until(uint32_t t0, uint32_t d) { while (clk() - t0 < d) {} }
__device__ __forceinline__ float ex2(float x) { float r; asm("ex2.approx.ftz.f32 %0,%1;" : "=f"(r) : "f"(x)); return r; }
__device__ __forceinline__ float silu(float x) { return __fdividef(x, 1.f + __expf(-x)); }
__device__ __forceinline__ float rbf(float x) { return __bfloat162float(__float2bfloat16_rn(x)); }

__device__ __forceinline__ void wgmma_ss_n128(float* d, uint64_t a, uint64_t b, int sd) {
  asm volatile("{.reg .pred p; setp.ne.b32 p, %66, 0;\n"
    "wgmma.mma_async.sync.aligned.m64n128k16.f32.bf16.bf16 {%0,%1,%2,%3,%4,%5,%6,%7,%8,%9,%10,%11,%12,%13,%14,%15,%16,%17,%18,%19,%20,%21,%22,%23,%24,%25,%26,%27,%28,%29,%30,%31,%32,%33,%34,%35,%36,%37,%38,%39,%40,%41,%42,%43,%44,%45,%46,%47,%48,%49,%50,%51,%52,%53,%54,%55,%56,%57,%58,%59,%60,%61,%62,%63}, %64, %65, p, 1, 1, 0, 1;}\n"
    : "+f"(d[0]),"+f"(d[1]),"+f"(d[2]),"+f"(d[3]),"+f"(d[4]),"+f"(d[5]),"+f"(d[6]),"+f"(d[7]),
      "+f"(d[8]),"+f"(d[9]),"+f"(d[10]),"+f"(d[11]),"+f"(d[12]),"+f"(d[13]),"+f"(d[14]),"+f"(d[15]),
      "+f"(d[16]),"+f"(d[17]),"+f"(d[18]),"+f"(d[19]),"+f"(d[20]),"+f"(d[21]),"+f"(d[22]),"+f"(d[23]),
      "+f"(d[24]),"+f"(d[25]),"+f"(d[26]),"+f"(d[27]),"+f"(d[28]),"+f"(d[29]),"+f"(d[30]),"+f"(d[31]),
      "+f"(d[32]),"+f"(d[33]),"+f"(d[34]),"+f"(d[35]),"+f"(d[36]),"+f"(d[37]),"+f"(d[38]),"+f"(d[39]),
      "+f"(d[40]),"+f"(d[41]),"+f"(d[42]),"+f"(d[43]),"+f"(d[44]),"+f"(d[45]),"+f"(d[46]),"+f"(d[47]),
      "+f"(d[48]),"+f"(d[49]),"+f"(d[50]),"+f"(d[51]),"+f"(d[52]),"+f"(d[53]),"+f"(d[54]),"+f"(d[55]),
      "+f"(d[56]),"+f"(d[57]),"+f"(d[58]),"+f"(d[59]),"+f"(d[60]),"+f"(d[61]),"+f"(d[62]),"+f"(d[63])
    : "l"(a), "l"(b), "r"(sd));
}
__device__ __forceinline__ void wgmma_ss_n192(float* d, uint64_t a, uint64_t b, int sd) {
  asm volatile("{.reg .pred p; setp.ne.b32 p, %98, 0;\n"
    "wgmma.mma_async.sync.aligned.m64n192k16.f32.bf16.bf16 {%0,%1,%2,%3,%4,%5,%6,%7,%8,%9,%10,%11,%12,%13,%14,%15,%16,%17,%18,%19,%20,%21,%22,%23,%24,%25,%26,%27,%28,%29,%30,%31,%32,%33,%34,%35,%36,%37,%38,%39,%40,%41,%42,%43,%44,%45,%46,%47,%48,%49,%50,%51,%52,%53,%54,%55,%56,%57,%58,%59,%60,%61,%62,%63,%64,%65,%66,%67,%68,%69,%70,%71,%72,%73,%74,%75,%76,%77,%78,%79,%80,%81,%82,%83,%84,%85,%86,%87,%88,%89,%90,%91,%92,%93,%94,%95}, %96, %97, p, 1, 1, 0, 1;}\n"
    : "+f"(d[0]),"+f"(d[1]),"+f"(d[2]),"+f"(d[3]),"+f"(d[4]),"+f"(d[5]),"+f"(d[6]),"+f"(d[7]),
      "+f"(d[8]),"+f"(d[9]),"+f"(d[10]),"+f"(d[11]),"+f"(d[12]),"+f"(d[13]),"+f"(d[14]),"+f"(d[15]),
      "+f"(d[16]),"+f"(d[17]),"+f"(d[18]),"+f"(d[19]),"+f"(d[20]),"+f"(d[21]),"+f"(d[22]),"+f"(d[23]),
      "+f"(d[24]),"+f"(d[25]),"+f"(d[26]),"+f"(d[27]),"+f"(d[28]),"+f"(d[29]),"+f"(d[30]),"+f"(d[31]),
      "+f"(d[32]),"+f"(d[33]),"+f"(d[34]),"+f"(d[35]),"+f"(d[36]),"+f"(d[37]),"+f"(d[38]),"+f"(d[39]),
      "+f"(d[40]),"+f"(d[41]),"+f"(d[42]),"+f"(d[43]),"+f"(d[44]),"+f"(d[45]),"+f"(d[46]),"+f"(d[47]),
      "+f"(d[48]),"+f"(d[49]),"+f"(d[50]),"+f"(d[51]),"+f"(d[52]),"+f"(d[53]),"+f"(d[54]),"+f"(d[55]),
      "+f"(d[56]),"+f"(d[57]),"+f"(d[58]),"+f"(d[59]),"+f"(d[60]),"+f"(d[61]),"+f"(d[62]),"+f"(d[63]),
      "+f"(d[64]),"+f"(d[65]),"+f"(d[66]),"+f"(d[67]),"+f"(d[68]),"+f"(d[69]),"+f"(d[70]),"+f"(d[71]),
      "+f"(d[72]),"+f"(d[73]),"+f"(d[74]),"+f"(d[75]),"+f"(d[76]),"+f"(d[77]),"+f"(d[78]),"+f"(d[79]),
      "+f"(d[80]),"+f"(d[81]),"+f"(d[82]),"+f"(d[83]),"+f"(d[84]),"+f"(d[85]),"+f"(d[86]),"+f"(d[87]),
      "+f"(d[88]),"+f"(d[89]),"+f"(d[90]),"+f"(d[91]),"+f"(d[92]),"+f"(d[93]),"+f"(d[94]),"+f"(d[95])
    : "l"(a), "l"(b), "r"(sd));
}
__device__ __forceinline__ void wgmma_ss_n256(float* d, uint64_t a, uint64_t b, int sd) {
  asm volatile("{.reg .pred p; setp.ne.b32 p, %130, 0;\n"
    "wgmma.mma_async.sync.aligned.m64n256k16.f32.bf16.bf16 {%0,%1,%2,%3,%4,%5,%6,%7,%8,%9,%10,%11,%12,%13,%14,%15,%16,%17,%18,%19,%20,%21,%22,%23,%24,%25,%26,%27,%28,%29,%30,%31,%32,%33,%34,%35,%36,%37,%38,%39,%40,%41,%42,%43,%44,%45,%46,%47,%48,%49,%50,%51,%52,%53,%54,%55,%56,%57,%58,%59,%60,%61,%62,%63,%64,%65,%66,%67,%68,%69,%70,%71,%72,%73,%74,%75,%76,%77,%78,%79,%80,%81,%82,%83,%84,%85,%86,%87,%88,%89,%90,%91,%92,%93,%94,%95,%96,%97,%98,%99,%100,%101,%102,%103,%104,%105,%106,%107,%108,%109,%110,%111,%112,%113,%114,%115,%116,%117,%118,%119,%120,%121,%122,%123,%124,%125,%126,%127}, %128, %129, p, 1, 1, 0, 1;}\n"
    : "+f"(d[0]),"+f"(d[1]),"+f"(d[2]),"+f"(d[3]),"+f"(d[4]),"+f"(d[5]),"+f"(d[6]),"+f"(d[7]),
      "+f"(d[8]),"+f"(d[9]),"+f"(d[10]),"+f"(d[11]),"+f"(d[12]),"+f"(d[13]),"+f"(d[14]),"+f"(d[15]),
      "+f"(d[16]),"+f"(d[17]),"+f"(d[18]),"+f"(d[19]),"+f"(d[20]),"+f"(d[21]),"+f"(d[22]),"+f"(d[23]),
      "+f"(d[24]),"+f"(d[25]),"+f"(d[26]),"+f"(d[27]),"+f"(d[28]),"+f"(d[29]),"+f"(d[30]),"+f"(d[31]),
      "+f"(d[32]),"+f"(d[33]),"+f"(d[34]),"+f"(d[35]),"+f"(d[36]),"+f"(d[37]),"+f"(d[38]),"+f"(d[39]),
      "+f"(d[40]),"+f"(d[41]),"+f"(d[42]),"+f"(d[43]),"+f"(d[44]),"+f"(d[45]),"+f"(d[46]),"+f"(d[47]),
      "+f"(d[48]),"+f"(d[49]),"+f"(d[50]),"+f"(d[51]),"+f"(d[52]),"+f"(d[53]),"+f"(d[54]),"+f"(d[55]),
      "+f"(d[56]),"+f"(d[57]),"+f"(d[58]),"+f"(d[59]),"+f"(d[60]),"+f"(d[61]),"+f"(d[62]),"+f"(d[63]),
      "+f"(d[64]),"+f"(d[65]),"+f"(d[66]),"+f"(d[67]),"+f"(d[68]),"+f"(d[69]),"+f"(d[70]),"+f"(d[71]),
      "+f"(d[72]),"+f"(d[73]),"+f"(d[74]),"+f"(d[75]),"+f"(d[76]),"+f"(d[77]),"+f"(d[78]),"+f"(d[79]),
      "+f"(d[80]),"+f"(d[81]),"+f"(d[82]),"+f"(d[83]),"+f"(d[84]),"+f"(d[85]),"+f"(d[86]),"+f"(d[87]),
      "+f"(d[88]),"+f"(d[89]),"+f"(d[90]),"+f"(d[91]),"+f"(d[92]),"+f"(d[93]),"+f"(d[94]),"+f"(d[95]),
      "+f"(d[96]),"+f"(d[97]),"+f"(d[98]),"+f"(d[99]),"+f"(d[100]),"+f"(d[101]),"+f"(d[102]),"+f"(d[103]),
      "+f"(d[104]),"+f"(d[105]),"+f"(d[106]),"+f"(d[107]),"+f"(d[108]),"+f"(d[109]),"+f"(d[110]),"+f"(d[111]),
      "+f"(d[112]),"+f"(d[113]),"+f"(d[114]),"+f"(d[115]),"+f"(d[116]),"+f"(d[117]),"+f"(d[118]),"+f"(d[119]),
      "+f"(d[120]),"+f"(d[121]),"+f"(d[122]),"+f"(d[123]),"+f"(d[124]),"+f"(d[125]),"+f"(d[126]),"+f"(d[127])
    : "l"(a), "l"(b), "r"(sd));
}
__device__ __forceinline__ void wgmma_rs_n32(float* d, const uint32_t* a, uint64_t b, int sd) {
  asm volatile("{.reg .pred p; setp.ne.b32 p, %21, 0;\n"
    "wgmma.mma_async.sync.aligned.m64n32k16.f32.bf16.bf16 {%0,%1,%2,%3,%4,%5,%6,%7,%8,%9,%10,%11,%12,%13,%14,%15}, {%16,%17,%18,%19}, %20, p, 1, 1, 0;}\n"
    : "+f"(d[0]),"+f"(d[1]),"+f"(d[2]),"+f"(d[3]),"+f"(d[4]),"+f"(d[5]),"+f"(d[6]),"+f"(d[7]),
      "+f"(d[8]),"+f"(d[9]),"+f"(d[10]),"+f"(d[11]),"+f"(d[12]),"+f"(d[13]),"+f"(d[14]),"+f"(d[15])
    : "r"(a[0]), "r"(a[1]), "r"(a[2]), "r"(a[3]), "l"(b), "r"(sd));
}
__device__ __forceinline__ void wgmma_ssT_n32(float* d, uint64_t a, uint64_t b, int sd) {
  asm volatile("{.reg .pred p; setp.ne.b32 p, %18, 0;\n"
    "wgmma.mma_async.sync.aligned.m64n32k16.f32.bf16.bf16 {%0,%1,%2,%3,%4,%5,%6,%7,%8,%9,%10,%11,%12,%13,%14,%15}, %16, %17, p, 1, 1, 1, 0;}\n"
    : "+f"(d[0]),"+f"(d[1]),"+f"(d[2]),"+f"(d[3]),"+f"(d[4]),"+f"(d[5]),"+f"(d[6]),"+f"(d[7]),
      "+f"(d[8]),"+f"(d[9]),"+f"(d[10]),"+f"(d[11]),"+f"(d[12]),"+f"(d[13]),"+f"(d[14]),"+f"(d[15])
    : "l"(a), "l"(b), "r"(sd));
}

__device__ __forceinline__ void wgmma_rs_n32_z(float* d, const uint32_t* a, uint64_t b) {
  asm volatile("{.reg .pred p; setp.ne.b32 p, 0, 0;\n"
    "wgmma.mma_async.sync.aligned.m64n32k16.f32.bf16.bf16 {%0,%1,%2,%3,%4,%5,%6,%7,%8,%9,%10,%11,%12,%13,%14,%15}, {%16,%17,%18,%19}, %20, p, 1, 1, 0;}\n"
    : "=f"(d[0]),"=f"(d[1]),"=f"(d[2]),"=f"(d[3]),"=f"(d[4]),"=f"(d[5]),"=f"(d[6]),"=f"(d[7]),
      "=f"(d[8]),"=f"(d[9]),"=f"(d[10]),"=f"(d[11]),"=f"(d[12]),"=f"(d[13]),"=f"(d[14]),"=f"(d[15])
    : "r"(a[0]), "r"(a[1]), "r"(a[2]), "r"(a[3]), "l"(b));
}

namespace rec {
constexpr int NVR = 5;
constexpr int NVS = 16 - NVR;
constexpr int NVP = 2;
constexpr int NWP = NWQ;
constexpr uint32_t WO = 0;
constexpr uint32_t XB = 65536;
constexpr uint32_t PK = XB + 32768;
constexpr uint32_t VN = PK + 24576;
constexpr uint32_t VX0 = VN + 4096;
constexpr uint32_t WVS = 131072;
constexpr uint32_t MEM = WVS + 2 * NVS * 2048;
constexpr uint32_t ARO = MEM + 10240;
constexpr uint32_t OB = ARO + 5120;
constexpr uint32_t QT = OB + 2048;
constexpr uint32_t KT = QT + 2048;
constexpr uint32_t RQ = KT + 6144;
constexpr uint32_t RK = RQ + 2048;
constexpr uint32_t SC = RK + 2048;
constexpr uint32_t OT = OB;
constexpr uint32_t SCT = 768, TFP = 9 * 128;
constexpr uint32_t TF = SC + 2 * SCT;
constexpr uint32_t PRE = MEM + 2 * NVR * 2048;
constexpr uint32_t TA = TF + 8 * TFP;
constexpr uint32_t RX = TA + 7168;
constexpr uint32_t VX1 = RX + 2048;
constexpr uint32_t BARS = VX1 + 4096;
constexpr uint32_t PACE = BARS + 18 * 8;
constexpr uint32_t SMEM = BARS + 512;
static_assert(PRE + 3072 <= TF, "staging");
constexpr int NW1 = NWA;
static_assert(SMEM <= 232448, "smem");
constexpr uint32_t T_MEM = 0, T_QK = 128, T_O = 256, T_WV = 384, T_WO = 512, T_AR = 640, T_PK = 768, T_VM = 896, T_RX = 1024;
constexpr int B_E = 2, B_SC = 3, B_S = 4, B_O = 5, B_F = 6, B_W = 7, B_C = 9, B_K = 10, B_H = 15, B_T0 = 0, B_Q = 1, B_S2 = 6, B_T2 = 9, B_P = 13, B_T = 14, B_R = 11, B_X = 12, B_V = 8;
constexpr int XC = 16384, X_RING = 131072, X_SC = 65536, X_TOK = 4096;
#define X_VX(i) (((i) >> 1) * 2048 + ((i) & 1) * 512)
#define X_VM(i) (X_VX(i) + 1024)
#define X_VRING(n) (((n) & 1) * X_RING + ((n) & 2) * 4096)
#define X_VTAG(n) ((((n) >> 2) + 1) & 1)
}
struct RecMaps { CUtensorMap wq, wk, wv, wo, ari, vx, wm, wm3, hst; int zero[40]; };

#define F_(x) __uint_as_float(x)
#define U_(x) __float_as_uint(x)
__device__ __forceinline__ void ar_fetch(uint32_t dst, const CUtensorMap* m, int slot, int half, uint32_t mb) {
  asm volatile("{.reg .pred p; elect.sync _|p, 0xffffffff; @p mbarrier.arrive.expect_tx.shared.b64 _,[%4],10240;\n"
               "@p cp.async.bulk.tensor.2d.shared::cluster.global.mbarrier::complete_tx::bytes [%0],[%1,{%2,%3}],[%4];\n"
               "@p cp.async.bulk.tensor.2d.shared::cluster.global.mbarrier::complete_tx::bytes [%0+5120],[%1,{%2,%5}],[%4];}"
               ::"r"(dst), "l"(m), "r"(slot * 64), "r"(half * 80), "r"(mb), "r"(half * 80 + 40) : "memory");
}
__device__ __forceinline__ uint4 exch_b128(void* p, uint32_t x, uint32_t y, uint32_t z, uint32_t w) {
  uint4 v;
  asm volatile("{.reg .b128 s, t; .reg .b64 a,b; mov.b64 a,{%5,%6}; mov.b64 b,{%7,%8}; mov.b128 s,{a,b}; atom.relaxed.gpu.global.exch.b128 t,[%4],s;"
               " mov.b128 {a,b},t; mov.b64 {%0,%1},a; mov.b64 {%2,%3},b;}" : "=r"(v.x), "=r"(v.y), "=r"(v.z), "=r"(v.w) : "l"(p), "r"(x), "r"(y), "r"(z), "r"(w) : "memory");
  return v;
}
#define CONSUME(v) do { if ((v) == 0x7fc12345u) sts1(sb + rec::BARS + 96, 0); } while (0)
__device__ __forceinline__ uint2 ldg_b64(const void* p) { uint2 v; asm volatile("{.reg .b64 t; ld.relaxed.gpu.global.b64 t,[%2]; mov.b64 {%0,%1},t;}" : "=r"(v.x), "=r"(v.y) : "l"(p) : "memory"); return v; }
__device__ __forceinline__ void stg_b64(void* p, uint32_t x, uint32_t y) { asm volatile("{.reg .b64 t; mov.b64 t,{%1,%2}; st.relaxed.gpu.global.b64 [%0],t;}" ::"l"(p), "r"(x), "r"(y) : "memory"); }
__device__ __forceinline__ uint32_t tagbad(uint32_t x, uint32_t y, uint32_t tag) { uint32_t r; asm("lop3.b32 %0,%1,%2,%3,0x7e;" : "=r"(r) : "r"(x), "r"(y), "r"(tag)); return r; }

__device__ __forceinline__ bool anybad(uint32_t a, uint32_t b, uint32_t c, uint32_t d, uint32_t e, uint32_t f, uint32_t g, uint32_t h, uint32_t tag) {
  uint32_t r;
  asm volatile("{.reg .b32 t,u,v,w; .reg .pred p; lop3.b32 t,%1,%2,%9,0x7e; lop3.b32 u,%3,%4,%9,0x7e; lop3.b32 v,%5,%6,%9,0x7e; lop3.b32 w,%7,%8,%9,0x7e;"
               " lop3.b32 t,t,u,v,0xfe; lop3.b32 t,t,w,1,0xa8; setp.ne.u32 p,t,0; vote.sync.any.pred p,p,0xffffffff; selp.u32 %0,1,0,p;}"
               : "=r"(r) : "r"(a), "r"(b), "r"(c), "r"(d), "r"(e), "r"(f), "r"(g), "r"(h), "r"(tag));
  return r;
}
__device__ __forceinline__ bool anybad(uint32_t a, uint32_t b, uint32_t c, uint32_t d, uint32_t tag) {
  uint32_t r;
  asm volatile("{.reg .b32 t,u; .reg .pred p; lop3.b32 t,%1,%2,%5,0x7e; lop3.b32 u,%3,%4,%5,0x7e;"
               " lop3.b32 t,t,u,1,0xa8; setp.ne.u32 p,t,0; vote.sync.any.pred p,p,0xffffffff; selp.u32 %0,1,0,p;}"
               : "=r"(r) : "r"(a), "r"(b), "r"(c), "r"(d), "r"(tag));
  return r;
}
#define BADS(r) anybad(r[0].x, r[0].y, r[1].x, r[1].y, r[2].x, r[2].y, r[3].x, r[3].y, tag)
constexpr float SCS = 0.08838834764831845f * 1.4426950408889634f / 16.f;
__device__ __forceinline__ uint32_t pkh(float lo, float hi, uint32_t tag) {
  uint32_t r;
  asm("{.reg .b32 t; cvt.rn.satfinite.f16x2.f32 t,%1,%2; lop3.b32 %0,t,0xfffffffe,%3,0xea;}" : "=r"(r) : "f"(hi), "f"(lo), "r"(tag));
  return r;
}
__device__ __forceinline__ uint32_t addh(uint32_t a, uint32_t b) { uint32_t r; asm("add.rn.f16x2 %0,%1,%2;" : "=r"(r) : "r"(a), "r"(b)); return r; }
__device__ __forceinline__ float hlo(uint32_t v) { float r; asm("{.reg .b16 a,b; mov.b32 {a,b},%1; cvt.f32.f16 %0,a;}" : "=f"(r) : "r"(v)); return r; }
__device__ __forceinline__ float hhi(uint32_t v) { float r; asm("{.reg .b16 a,b; mov.b32 {a,b},%1; cvt.f32.f16 %0,b;}" : "=f"(r) : "r"(v)); return r; }
__device__ __forceinline__ uint32_t ordh(uint32_t v) {
  uint32_t r;
  asm("{.reg .b32 m; prmt.b32 m,%1,0,0xbb99; lop3.b32 %0,%1,m,0x7fff7fff,0x78;}" : "=r"(r) : "r"(v));
  return r;
}
template <bool MASK>
__device__ __forceinline__ float4 softmax2(const uint2 (&r)[4], uint32_t mx, uint32_t my) {
  uint32_t x = addh(addh(r[0].x, r[1].x), addh(r[2].x, r[3].x)), y = addh(addh(r[0].y, r[1].y), addh(r[2].y, r[3].y)), k;
  if (MASK) x = addh(x, mx);
  y = addh(y, my);
  asm("max.f16x2 %0,%1,%2;" : "=r"(k) : "r"(x), "r"(y));
  k = ordh(k);
  const int k0 = __reduce_max_sync(~0u, (int)(k << 16)), k1 = __reduce_max_sync(~0u, (int)k);
  k = ordh(__byte_perm(k0, k1, 0x7632));
  const float m0 = hlo(k) * -16.f, m1 = hhi(k) * -16.f;
  return make_float4(ex2(fmaf(hlo(x), 16.f, m0)), ex2(fmaf(hhi(x), 16.f, m1)), ex2(fmaf(hlo(y), 16.f, m0)), ex2(fmaf(hhi(y), 16.f, m1)));
}
__device__ __forceinline__ char* mkp(uint32_t lo, uint32_t hi) { uint64_t r; asm("mov.b64 %0,{%1,%2};" : "=l"(r) : "r"(lo), "r"(hi)); return (char*)r; }
#define LO(p) ((uint32_t)(uint64_t)(p))
#define HI(p) ((uint32_t)((uint64_t)(p) >> 32))
__device__ __forceinline__ uint32_t addbf(uint32_t a, uint32_t b) { uint32_t r; asm("add.rn.bf16x2 %0,%1,%2;" : "=r"(r) : "r"(a), "r"(b)); return r; }
__device__ __forceinline__ void pv_mem(const uint32_t (&p)[4], uint32_t pm, const uint4 (&v)[4], const uint4 (&vn)[2], uint32_t (&O)[4], uint32_t sums, uint32_t l16) {
  float o[4][4] = {{0, 0, 0, 0}, {0, 0, 0, 0}, {0, 0, 0, 0}, {0, 0, 0, 0}}, sum[4] = {0, 0, 0, 0};
  const uint32_t one = 0x3f803f80u;
  if (ASM) mma8(sum, one, one, pm);
  mma16(o[0], v[0].x, v[0].y, v[0].z, v[0].w, p[0], p[1]);
  mma16(o[1], v[2].x, v[2].y, v[2].z, v[2].w, p[0], p[1]);
  mma16(o[2], v[1].x, v[1].y, v[1].z, v[1].w, p[2], p[3]);
  mma16(o[3], v[3].x, v[3].y, v[3].z, v[3].w, p[2], p[3]);
  if (ASM) mma16(sum, one, one, one, one, p[0], p[1]);
  mma16(o[0], vn[0].x, vn[0].y, vn[0].z, vn[0].w, pm, pm);
  mma16(o[1], vn[1].x, vn[1].y, vn[1].z, vn[1].w, pm, pm);
  if (ASM) {
    mma16(sum, one, one, one, one, p[2], p[3]);
    asm volatile("{.reg .pred p; .reg .b32 t; and.b32 t,%3,0x1c0; setp.eq.u32 p,t,0; @p st.shared.v2.f32 [%0],{%1,%2};}" ::"r"(sums), "f"(sum[0]), "f"(sum[1]), "r"(l16) : "memory");
  }
  O[0] = pk(o[0][0] + o[2][0], o[0][1] + o[2][1]); O[1] = pk(o[0][2] + o[2][2], o[0][3] + o[2][3]);
  O[2] = pk(o[1][0] + o[3][0], o[1][1] + o[3][1]); O[3] = pk(o[1][2] + o[3][2], o[1][3] + o[3][3]);
}
__device__ __forceinline__ void pv_tok(const uint32_t (&p)[4], uint32_t pm, const uint4 (&v)[4], const uint32_t (&vm)[4], uint32_t (&O)[4]) {
  float o[2][4] = {{0, 0, 0, 0}, {0, 0, 0, 0}}, sum[4] = {0, 0, 0, 0};
  const uint32_t one = 0x3f803f80u;
  mma16(sum, one, one, one, one, p[0], p[1]);
  mma16(o[0], v[0].x, v[0].y, v[0].z, v[0].w, p[0], p[1]);
  mma16(o[1], v[2].x, v[2].y, v[2].z, v[2].w, p[0], p[1]);
  mma16(sum, one, one, one, one, p[2], p[3]);
  mma16(o[0], v[1].x, v[1].y, v[1].z, v[1].w, p[2], p[3]);
  mma16(o[1], v[3].x, v[3].y, v[3].z, v[3].w, p[2], p[3]);
  mma8(sum, one, one, pm);
  mma8(o[0], vm[0], vm[1], pm);
  mma8(o[1], vm[2], vm[3], pm);
  float i0, i1;
  asm("rcp.approx.ftz.f32 %0,%1;" : "=f"(i0) : "f"(sum[0]));
  asm("rcp.approx.ftz.f32 %0,%1;" : "=f"(i1) : "f"(sum[1]));
  O[0] = pk(o[0][0] * i0, o[0][1] * i1); O[1] = pk(o[0][2] * i0, o[0][3] * i1);
  O[2] = pk(o[1][0] * i0, o[1][1] * i1); O[3] = pk(o[1][2] * i0, o[1][3] * i1);
}
template <int OFF>
__device__ __forceinline__ void sta1(uint32_t a, uint32_t v, uint32_t mb) {
  asm volatile("st.async.shared::cluster.mbarrier::complete_tx::bytes.b32 [%0+%3],%1,[%2];" ::"r"(a), "r"(v), "r"(mb), "n"(OFF) : "memory");
}

__device__ __forceinline__ void rec_helper(char* smem, const bf16* x, const bf16* cvec, const CUtensorMap* wm) {
  const int tid = threadIdx.x, hb = blockIdx.x & 3;
  float4* md = (float4*)(smem + 12288);
  uint4* hs = (uint4*)(smem + 152 * 1024);
  uint4 xr[8];
  const uint4* px = (const uint4*)(x + (size_t)(hb * 16 + (tid >> 5) * 2) * 1024) + (tid & 31);
#pragma unroll
  for (int i = 0; i < 8; i++) xr[i] = __ldg(px + i * 32);
#pragma unroll 1
  for (int i = tid; i < 2560; i += 256) g_ar[hb * 2560 + i] = make_uint4(0, 0, 0, 0);
  g_tm[tid] = 0;
  g_oc[hb * 256 + tid] = 0;
  float4 mr[16];
#pragma unroll 1
  for (int k = 0; k < 32; k++) {
    float v[2][32], m[8] = {}, q[8] = {};
#pragma unroll
    for (int i = 0; i < 8; i++) {
      const uint4 u = xr[i];
      float* w = v[i >> 2] + (i & 3) * 8;
      w[0] = blo(u.x); w[1] = bhi(u.x); w[2] = blo(u.y); w[3] = bhi(u.y); w[4] = blo(u.z); w[5] = bhi(u.z); w[6] = blo(u.w); w[7] = bhi(u.w);
      xr[i] = __ldg(px + min(k + 1, 31) * 8192 + i * 32);
    }
#pragma unroll
    for (int i = 0; i < 64; i++) m[i & 7] += v[i & 1][i >> 1];
    m[0] = (m[0] + m[2]) + (m[4] + m[6]); m[1] = (m[1] + m[3]) + (m[5] + m[7]);
#pragma unroll
    for (int o = 16; o; o >>= 1) { m[0] += __shfl_xor_sync(~0u, m[0], o); m[1] += __shfl_xor_sync(~0u, m[1], o); }
    m[0] *= 1.f / 1024; m[1] *= 1.f / 1024;
#pragma unroll
    for (int i = 0; i < 64; i++) { float& w = v[i & 1][i >> 1]; w -= m[i & 1]; q[i & 7] += w * w; }
    q[0] = (q[0] + q[2]) + (q[4] + q[6]); q[1] = (q[1] + q[3]) + (q[5] + q[7]);
#pragma unroll
    for (int o = 16; o; o >>= 1) { q[0] += __shfl_xor_sync(~0u, q[0], o); q[1] += __shfl_xor_sync(~0u, q[1], o); }
    const float rstd[2] = {rsqrtf(q[0] * (1.f / 1024) + 1e-5f), rsqrtf(q[1] * (1.f / 1024) + 1e-5f)};
    if (k == 0) {
      PT(44);
#pragma unroll 1
      for (int i = 0; i < 2; i++) {
        uint4 p[4];
        int it = 0;
        while (true) {
#pragma unroll
          for (int u = 0; u < 4; u++) p[u] = ldg_rlx4(g_modp + u * 512 + i * 256 + tid);
          uint32_t ok = 1;
#pragma unroll
          for (int u = 0; u < 4; u++) ok &= p[u].x & p[u].y & p[u].z & p[u].w;
          if (__all_sync(~0u, ok)) break;
          if (++it > SPIN_LIMIT) __trap();
          __nanosleep(100);
        }
        md[i * 256 + tid] = make_float4(i + rbf((F_(p[0].x) + F_(p[1].x)) + (F_(p[2].x) + F_(p[3].x))), i + rbf((F_(p[0].y) + F_(p[1].y)) + (F_(p[2].y) + F_(p[3].y))),
                                        i + rbf((F_(p[0].z) + F_(p[1].z)) + (F_(p[2].z) + F_(p[3].z))), i + rbf((F_(p[0].w) + F_(p[1].w)) + (F_(p[2].w) + F_(p[3].w))));
      }
      BAR_SYNC(rec::B_F, 256);
#pragma unroll
      for (int i = 0; i < 16; i++) mr[i] = md[(i >> 3) * 256 + ((i >> 1) & 3) * 64 + (tid & 31) * 2 + (i & 1)];
      PT(45);
    }
#pragma unroll
    for (int i = 0; i < 4; i++) {
      const int ch = i * 32 + (tid & 31);
      const float4 s0 = mr[i * 2], s1 = mr[i * 2 + 1], c0 = mr[8 + i * 2], c1 = mr[9 + i * 2];
#pragma unroll
      for (int r = 0; r < 2; r++) {
        const int row = (tid >> 5) * 2 + r;
        const float* w = v[r] + i * 8;
        hs[(k & 1) * 2048 + (ch >> 3) * 128 + row * 8 + ((ch & 7) ^ (row & 7))] =
            make_uint4(pk(w[0] * rstd[r] * c0.x + s0.x, w[1] * rstd[r] * c0.y + s0.y), pk(w[2] * rstd[r] * c0.z + s0.z, w[3] * rstd[r] * c0.w + s0.w),
                       pk(w[4] * rstd[r] * c1.x + s1.x, w[5] * rstd[r] * c1.y + s1.y), pk(w[6] * rstd[r] * c1.z + s1.z, w[7] * rstd[r] * c1.w + s1.w));
      }
    }
    if (k == 0) PT(63);
    FENCE_ASYNC_SMEM();
    BAR_SYNC(rec::B_W, 288);
    if (k < 2) PT(46 + k * 12);
  }
  PT(59);
  PDUMP();
  const uint32_t sc = (uint32_t)__cvta_generic_to_shared(smem), wb = sc + 20480, mb = sc + rec::PACE;
#pragma unroll 1
  for (int i = tid; i < 512; i += 256) sts1(sc + i * 4, pk(silu(__bfloat162float(cvec[2 * i])), silu(__bfloat162float(cvec[2 * i + 1]))));
#pragma unroll 1
  for (int i = tid; i < 2048; i += 256) g_stat[hb * 2048 + i] = make_uint4(~0u, ~0u, ~0u, ~0u);
#pragma unroll 1
  for (int i = tid; i < 512; i += 256) g_cnt[hb * 512 + i] = 0;
  if (tid == 0 && hb == 0) g_fcnt = 0;
  if (tid == 0) asm volatile("{.reg .u32 t; mov.u32 t,%%smid; st.global.u32 [%0],t;}" ::"l"((unsigned*)g_hsm + hb) : "memory");
  BAR_SYNC(rec::B_O, 320);
  if (tid == 0) FT(37);
  const int lane = tid & 31;
  const uint32_t fa = wb + (tid >> 5) * 8192 + ((lane & 7) + (lane >> 4) * 8) * 128 + ((((lane >> 3) & 1) ^ (lane & 7)) << 4);
  float acc[2][4][4] = {};
#pragma unroll 1
  for (int i2 = -2; i2 < 32; i2 += 2) {
#pragma unroll
    for (int u = 0; u < 2; u++) {
      const int i = i2 + u;
      if (i < 30 && tid < 32) e_expect_tma3d<true>(wb + (i + 2) % 3 * 65536, wm, (i2 + 2) * 32, 32 + hb * 16 + u * 8, mb + (i + 2) % 3 * 8, 65536);
      if (i < 0) continue;
      mbar_wait(mb + i % 3 * 8, i / 3 & 1);
#pragma unroll
      for (int ks = 0; ks < 4; ks++) {
        const uint32_t b0 = lds1(sc + i2 * 64 + ks * 32 + (lane & 3) * 4), b1 = lds1(sc + i2 * 64 + ks * 32 + (lane & 3) * 4 + 16);
#pragma unroll
        for (int m = 0; m < 4; m++) {
          uint32_t a[4];
          ldsm4t(a, (fa ^ (m * 32)) + i % 3 * 65536 + ks * 2048);
          mma16(acc[u][m], a[0], a[1], a[2], a[3], b0, b1);
        }
      }
      FENCE_ASYNC_SMEM();
      BAR_SYNC(rec::B_F, 256);
    }
  }
  if (!(lane & 3)) {
#pragma unroll
    for (int i = 0; i < 16; i++) g_mod[2048 + hb * 1024 + (i >> 3) * 512 + (tid >> 5) * 64 + (i & 7) * 8 + (lane >> 2)] = rbf(acc[i >> 3][(i >> 1) & 3][(i & 1) * 2]);
  }
  BAR_SYNC(rec::B_F, 256);
  if (tid == 0) asm volatile("fence.acq_rel.gpu; griddepcontrol.launch_dependents;" ::: "memory");
  if (tid == 0) FT(33);
}

__global__ void __cluster_dims__(2, 1, 1) __launch_bounds__(512, 1)
k_rec(const __grid_constant__ RecMaps mp, const bf16* __restrict__ mem0, const bf16* __restrict__ x, const bf16* __restrict__ cvec,
      const bf16* __restrict__ wmod, const bf16* __restrict__ wo_g, char* xc, int dF, int dA, int dS, int dM, int dG, int dP, int dX, int dD, int dZ, int dZ2, int dV, int dX2) {
  using namespace rec;
  extern __shared__ __align__(1024) char smem[];
  const uint32_t sb = (uint32_t)__cvta_generic_to_shared(smem);
  if ((sb & 0x3FFFF) != 1024) __trap();
  PH(0);
  PZERO();
  if (threadIdx.x == 0) {
    int b = blockIdx.x;
    if (b >= 8 && b < 128) {
      const int t = (b >> 1) - 4, u = t - 32;
      b = 2 * (t < 32 ? 4 + (t & 16) + (t & 7) * 2 + ((t >> 3) & 1) : 36 + (u / 14) * 14 + (u % 7) * 2 + ((u / 7) & 1)) + (b & 1);
    }
    sts1(sb + rec::PACE + 24, b);
  }
#define ROLE_REFRESH { asm volatile("mov.u32 %0,%%tid.x;" : "=r"(tid)); wid = __shfl_sync(~0u, tid >> 5, 0); b = __shfl_sync(~0u, lds1(sb + PACE + 24), 0); }
#define ROLE_VARS int tid; asm volatile("mov.u32 %0,%%tid.x;" : "=r"(tid)); \
    int wid = __shfl_sync(~0u, tid >> 5, 0), b = __shfl_sync(~0u, lds1(sb + PACE + 24), 0);
#define wg (wid >> 2)
#define iw (wid & 3)
#define h (b >> 2)
#define j (b & 3)
#define a (b & 1)
#define bb ((b >> 1) & 1)
  const uint32_t wbar = sb + BARS + 48, obar = wbar + 8;
  if (threadIdx.x == 256) {
    for (int i = 0; i < 18; i++) if (i != 12) mbar_init(sb + BARS + i * 8, i == 3 || i == 8 || i == 9 || i == 10 ? 2 : 1);
    for (int i = 0; i < 3; i++) mbar_init(sb + PACE + i * 8, 1);
    asm volatile("fence.mbarrier_init.release.cluster;" ::: "memory");
    FENCE_ASYNC_SMEM();
    mbar_expect(sb + BARS, 2048);
    mbar_expect(sb + BARS + 16, 4096);
    mbar_expect(sb + BARS + 32, 4096);
    mbar_expect(sb + BARS + 40, 4096);
  }
  __syncthreads();
#define lane ((int)(l16 >> 4))
#define l16 (L16 & 0x1f0)
#define PIN(x) __shfl_xor_sync(~0u, (uint32_t)(x), 0)
#define lpub ((L16 & 0x30) * 64 + ((L16 >> 3) & 0x38))
#define lrow ((L16 & 0x70) + (((L16 >> 3) ^ L16) & 0x70 & ~((L16 >> 3) & 0x40) ? L16 & 0x180 : 512))

  const int role = __shfl_sync(~0u, threadIdx.x >> 7, 0);
  if (role < 2) {
    asm volatile("setmaxnreg.inc.sync.aligned.u32 %0;" ::"n"(RF_));
    if (blockIdx.x >= 128) { rec_helper(smem, x, cvec, &mp.wm3); return; }
    ROLE_VARS
    uint32_t L16 = __shfl_sync(~0u, sb + (tid & 31) * 16, tid & 31);
    {
      uint4 wm[8];
      const uint4* pw = (const uint4*)(wmod + (size_t)((b >> 5) * 256 + (tid >> 3)) * 6144 + (b & 31) * 64) + (tid & 7);
      const float cs = __bfloat162float(cvec[(b >> 5) * 256 + tid]);
#pragma unroll
      for (int i = 0; i < 8; i++) wm[i] = __ldcs(pw + (size_t)i * 32 * 768);
      float* sc = (float*)(smem + PRE);
      sc[tid] = rbf(silu(cs));
      BAR_SYNC(B_F, 256);
      PT(42);
      float acc[8] = {0, 0, 0, 0, 0, 0, 0, 0};
#pragma unroll
      for (int i = 0; i < 8; i++) {
        const float f = sc[i * 32 + (tid >> 3)];
        acc[0] += f * blo(wm[i].x); acc[1] += f * bhi(wm[i].x); acc[2] += f * blo(wm[i].y); acc[3] += f * bhi(wm[i].y);
        acc[4] += f * blo(wm[i].z); acc[5] += f * bhi(wm[i].z); acc[6] += f * blo(wm[i].w); acc[7] += f * bhi(wm[i].w);
      }
#pragma unroll
      for (int i = 0; i < 8; i++) { acc[i] += __shfl_xor_sync(~0u, acc[i], 8); acc[i] += __shfl_xor_sync(~0u, acc[i], 16); }
      float* red = sc + 256;
      if ((tid & 31) < 8) {
#pragma unroll
        for (int i = 0; i < 8; i++) red[(tid >> 5) * 64 + (tid & 7) * 8 + i] = acc[i];
      }
      BAR_SYNC(B_F, 256);
      if (tid < 64) {
        float t = 0;
#pragma unroll
        for (int i = 0; i < 8; i++) t += red[i * 64 + tid];
        asm volatile("st.relaxed.gpu.global.u32 [%0],%1;" ::"l"((unsigned*)g_modp + (b >> 5) * 2048 + (b & 31) * 64 + tid), "r"(U_(t) | 1u) : "memory");
      }
      PH(1); PT(43);
    }
    uint32_t m0[2][4];
#pragma unroll
    for (int i = 0; i < 2; i++)
#pragma unroll
      for (int r = 0; r < 4; r++)
        m0[i][r] = (uint32_t)__bfloat16_as_ushort(mem0[(2 * r) * 1024 + a * 512 + tid * 2 + i]) | ((uint32_t)__bfloat16_as_ushort(mem0[(2 * r + 1) * 1024 + a * 512 + tid * 2 + i]) << 16);
    ROLE_REFRESH
    uint32_t wQ[16][4], wK[16][4], wV[NVR][4];
    uint32_t frag = sb + ((lane & 7) + (lane >> 4) * 8) * 128 + (((iw * 2 + ((lane >> 3) & 1)) ^ (lane & 7)) << 4);
    mbar_wait(wbar, 0);
    PH(2); PT(48);
#pragma unroll
    for (int i = 0; i < 16; i++) { ldsm4t(wQ[i], frag + WO + wg * 32768 + i * 2048); ldsm4t(wK[i], frag + XB + wg * 32768 + i * 2048); }
    FENCE_ASYNC_SMEM();
    PH(3); PT(49);
    CLUSTER_SYNC();
    PT(50);
    auto x_load = [&](int n) {
      asm volatile("{.reg .pred p; elect.sync _|p, 0xffffffff; @p mbarrier.arrive.expect_tx.shared.b64 _,[%2],32768;\n"
                   "@p cp.async.bulk.shared::cluster.global.mbarrier::complete_tx::bytes [%0],[%1],32768,[%2];}"
                   ::"r"(sb + (X1 && n ? WO : XB)), "l"(g_h + n * 4096 + a * 2048), "r"(sb + BARS + (X1 && n ? 120 : 136)) : "memory");
    };
    if (wid == 0) {
      wait_h(0);
      PT(47);
      x_load(0);
      if (X1) { wait_until(clk(), XD1); x_load(1); }
    }
#define owner ((iw >> 1) == a)
#define oi (wid & 1)
    frag += wg * NVS * 2048;
    {
      const uint32_t rsb = mapa(sb, iw >> 1);
      const uint32_t pp = rsb + PK + (owner ? 0 : 12288) + (oi * 2048 + wg * 1024) + l16;
      const uint32_t mb = sb + MEM + wg * 5120;
      const uint32_t t = sb + TF + wid * TFP + lane * 4;
      sts1(t + T_MEM, mb + lrow);
      sts1(t + T_QK, owner ? L16 + (lane >> 4) * (RK - RQ - 256) + RQ + oi * 1024 + wg * 256 : rsb + RQ + oi * 1024 + 512 + wg * 256 + (l16 >> 2));
      sts1(t + T_O, L16 + OB);
      sts1(t + T_WV, frag);
      sts1(t + T_WO, sb + WO + (wid >> 1) * 16384 + ((lane & 7) + (lane >> 4) * 8) * 128 + ((((wid & 1) * 4 + ((lane >> 3) & 1)) ^ (lane & 7)) << 4));
      sts1(t + T_AR, sb + ARO + wid * 640 + lrow);
      sts1(t + T_PK, pp);
      sts1(t + T_VM, LO(xc) + h * 262144 + (bb * 2 + (iw >> 1)) * XC + X_VM(0) + oi * 2048 + a * 256 + (l16 >> 1));
      sts1(t + T_RX, L16 + RX + iw * 512);
    }
    uint32_t tp = sb + TF + wid * TFP + lane * 4;
    if (!wg) {
      const uint32_t xo = lds1(tp + T_VM);
      stg_b64(mkp(xo, HI(xc)), 0, 0); stg_b64(mkp(xo + X_RING, HI(xc)), 0, 0);
    }
    int wo_ = __shfl_sync(~0u, owner + wg * 2, 0);
    auto park_ptr = [&]() { return lds1(tp + T_PK); };
    auto park = [&](const float* f, int m, int n, uint32_t d) {
      uint32_t w[8];
#pragma unroll
      for (int i = 0; i < 8; i++) w[i] = pk(f[2 * i], f[2 * i + 1]);
      if (wo_ & 1) {
        sts4(d + m * 4096, w[0], w[1], w[2], w[3]); sts4(d + m * 4096 + 512, w[4], w[5], w[6], w[7]);
      } else {
        const uint32_t pb = (d & 0xff000000u) + 1024 + BARS + (m ? 24 + m * 8 : 16);
        {
          sta4(d + m * 4096, w, pb); sta4(d + m * 4096 + 512, w + 4, pb);
        }
      }
    };
    auto xdesc = [&](int n) { return mkdesc(__shfl_sync(~0u, 1024 + (X1 && n == 1 ? WO : XB) + wg * 16384, 0), 16, 1024); };
    uint64_t xpre = 0;
    auto rs_issue = [&](float* acc, const uint32_t (&w)[16][4], int n, bool fence, bool pre = false) {
      const uint64_t x = pre ? xpre : xdesc(n);
      if (fence) WG_FENCE();
      wgmma_rs_n32_z(acc, w[0], x);
#pragma unroll
      for (int i = 1; i < 16; i++) wgmma_rs_n32(acc, w[i], x + (i >> 2) * 256 + (i & 3) * 2, 1);
      WG_COMMIT();
    };
    auto v_issue = [&](float* acc, int n, bool fence) {
      const uint64_t dv = mkdesc(__shfl_sync(~0u, 1024 + WVS + wg * NVS * 2048, 0), 16, 1024), x = xdesc(n);
      if (fence) WG_FENCE();
      wgmma_rs_n32_z(acc, wV[0], x);
#pragma unroll
      for (int i = NVR; i < 16; i++) wgmma_ssT_n32(acc, dv + (i - NVR) * 128, x + (i >> 2) * 256 + (i & 3) * 2, 1);
#pragma unroll
      for (int i = 1; i < NVR; i++) wgmma_rs_n32(acc, wV[i], x + (i >> 2) * 256 + (i & 3) * 2, 1);
      WG_COMMIT();
    };
    uint32_t mA;
    auto vk_pass = [&](int n, uint32_t d, bool pro) {
      float acc[16], acc2[16];
      if (VW) rs_issue(acc, wQ, pro ? n : 0, true); else v_issue(acc, pro ? n : 0, true);
      rs_issue(acc2, wK, pro ? n : 0, false);
      if (n > 0) mbar_wait(sb + BARS + 80, (n - 1) & 1);
      WG_WAIT(1);
      park(acc, 2, n, d);
      mA = lds1(tp + T_MEM);
      BAR_ARRIVE(B_K, 320);
      WG_WAIT(0);
      park(acc2, 1, n, d);
    };
    auto wo_load = [&](int i0, int i1) {
      if (i1 == 4) asm volatile("{.reg .pred p; elect.sync _|p, 0xffffffff; @p mbarrier.arrive.expect_tx.shared.b64 _,[%0],65536;}" ::"r"(obar) : "memory");
#pragma unroll
      for (int i = i0; i < i1; i++)
        asm volatile("{.reg .pred p; elect.sync _|p, 0xffffffff; @p cp.async.bulk.tensor.2d.shared::cluster.global.mbarrier::complete_tx::bytes [%0],[%1,{%2,%3}],[%4];}"
                     ::"r"(sb + WO + i * 16384), "l"(&mp.wo), "r"(j * 256 + i * 64), "r"(h * 128), "r"(obar) : "memory");
    };
    {
#pragma unroll 1
      for (int n = 0; n < 2; n++) {
        float acc[16];
        asm volatile("" : "+r"(wid), "+r"(wo_));
        if (X1) mbar_wait(sb + BARS + 136 - n * 16, 0); else mbar_wait(sb + BARS + 136, n);
        PT(51 + n * 3);
        if (!X1 && n == 1 && wid == 0) wo_load(0, 4);
        if (X1 && n == 1 && wid == 0) wo_load(2, 4);
        if (!VW) {
          rs_issue(acc, wQ, n, true);
          if (n > 0) mbar_wait(sb + BARS + 24, 0);
          WG_WAIT(0);
          park(acc, 0, n, park_ptr());
        }
        if (!n) {
          mbar_wait(sb + BARS + 88, 0);
          PT(60);
#pragma unroll
          for (int i = 0; i < NVR; i++) ldsm4t(wV[i], frag + MEM + (wg * (NVR - NVS) + i) * 2048);
          BAR_SYNC(B_H, 256);
#pragma unroll
          for (int i = 0; i < 2; i++) {
            const int k = tid * 2 + i, m = (k >> 3) & 3, r = k & 7;
            sts4(sb + MEM + (k >> 5) * 640 + (r == m ? 512 : m * 128) + r * 16, m0[i][0], m0[i][1], m0[i][2], m0[i][3]);
          }
          if (lane < 8) {
            sts4(sb + ARO + wid * 640 + (lane < 4 ? lane * 144 : 512 + l16), 0x3f803f80, 0x3f803f80, 0x3f803f80, 0x3f803f80);
#pragma unroll
            for (int i = 0; i < 2; i++) sts4(sb + MEM + (wid * 2 + i) * 640 + (lane < 4 ? lane * 144 : 512 + l16), 0x42004200, 0x42004200, 0x42004200, 0x42004200);
          }
        }
        if (VW) {
          v_issue(acc, n, true);
          if (n > 0) mbar_wait(sb + BARS + 24, 0);
          if (X1 && n > 0) BAR_SYNC(B_H, 320);
          WG_WAIT(0);
          park(acc, 0, n, park_ptr());
        }
        PT(52 + n * 3);
        BAR_ARRIVE(B_C, 320);
        vk_pass(n, park_ptr(), true);
        PT(53 + n * 3);
        if (n > 0) break;
        BAR_ARRIVE(B_X, 320);
        if (X1) { BAR_ARRIVE(B_Q, 288); continue; }
        BAR_SYNC(B_H, 256);
        if (wid == 0) x_load(1);
        BAR_SYNC(B_C, 320);
      }
      BAR_ARRIVE(B_P, 384); BAR_ARRIVE(B_X, 320);
      if (!X1) BAR_ARRIVE(B_Q, 288);
      BAR_SYNC(B_T0, 320);
      if (X1 && wid == 0) wo_load(0, 2);
    }
    PH(4);
    PT(57);
    ROLE_REFRESH
    for (int s = 0; s < 64; s++) {
      asm volatile("" : "+r"(tp), "+r"(wo_));
      wid = wo_ * 2;
      uint32_t vS[NVS][4], bf[8][4], rm;
      if (s > 0) BAR_SYNC(B_R, 320);
#define VMMA(c, w, i) mma16(c, (w)[0], (w)[1], (w)[2], (w)[3], bf[(i) >> 1][((i) & 1) * 2], bf[(i) >> 1][((i) & 1) * 2 + 1])
      {
        float cQ[4] = {0, 0, 0, 0}, cK[4] = {0, 0, 0, 0}, dQ[4] = {0, 0, 0, 0}, dK[4] = {0, 0, 0, 0};
#pragma unroll
        for (int t = 7; t >= 8 - NB1; t--) ldsm4t(bf[t], mA + t * 640);
        SCHED_FENCE(47);
#pragma unroll
        for (int i = 15; i >= 0; i--) {
          if (i & 1) { VMMA(dQ, wQ[i], i); VMMA(dK, wK[i], i); } else { VMMA(cQ, wQ[i], i); VMMA(cK, wK[i], i); }
          if (i == 0) {
#pragma unroll
            for (int e = 0; e < 4; e++) { cQ[e] += dQ[e]; cK[e] += dK[e]; }
          }
          if (i == IB2 && NB2) {
            SCHED_FENCE(49);
#pragma unroll
            for (int t = 7 - NB1; t >= 8 - NB1 - NB2; t--) ldsm4t(bf[t], mA + t * 640);
          }
          if (i == IB3) {
            if (NB1 + NB2 < 8) SCHED_FENCE(51);
#pragma unroll
            for (int t = 7 - NB1 - NB2; t >= 0; t--) ldsm4t(bf[t], mA + t * 640);
            rm = lds1(tp + T_QK); frag = lds1(tp + T_WV);
          }
          if (i == IV) {
#pragma unroll
            for (int u = 0; u < NVP; u++) ldsm4t(vS[NVS - 1 - u], frag + WVS + (NVS - 1 - u) * 2048);
          }
        }
        const uint32_t w0 = pk(cQ[0] * SCS, cQ[1] * SCS), w1 = pk(cQ[2] * SCS, cQ[3] * SCS), w2 = pk(cK[0], cK[1]), w3 = pk(cK[2], cK[3]);
        if (wo_ & 1) {
          stsm4(rm, w0, w1, w2, w3);
          BAR_ARRIVE(B_E, 256);
        } else {
          const uint32_t mm = (rm & 0xff000000u) + 1024 + BARS;
          sta1<0>(rm, w0, mm); sta1<128>(rm, w1, mm);
          sta1<RK - RQ>(rm, w2, mm); sta1<RK - RQ + 128>(rm, w3, mm);
        }
        if (tp - sb - TF < 3 * TFP && tp - sb - TF >= 2 * TFP) TS(0);
      }
      uint32_t oA, woA;
      {
        float cV[4] = {0, 0, 0, 0}, cW[4] = {0, 0, 0, 0};
        static_assert(NVP == 2 && NVR == 5, "schedule");
#define VLD(k) ldsm4t(vS[(k) - NVR], frag + WVS + ((k) - NVR) * 2048)
#define VS_(c, k) VMMA(c, vS[(k) - NVR], k)
        const uint32_t ex = lds1(tp + T_RX), xv = lds1(tp + T_VM);
        VLD(13);
        VS_(cW, 15); VS_(cV, 14); VLD(12); VLD(11); VMMA(cW, wV[4], 4); VMMA(cV, wV[3], 3); VLD(10); VMMA(cW, wV[2], 2); VLD(9);
        VMMA(cV, wV[1], 1); VLD(8); VMMA(cW, wV[0], 0); VLD(7); VS_(cV, 13); VLD(6); VS_(cW, 12); VLD(5);
        VS_(cV, 11); VS_(cW, 10); VS_(cV, 9); VS_(cW, 8); VS_(cV, 7); VS_(cW, 6); VS_(cV, 5);
#pragma unroll
        for (int e = 0; e < 4; e++) cV[e] += cW[e];
        woA = lds1(tp + T_WO);
        oA = lds1(tp + T_O + (s & dZ));
        if (wg) {
          sts4(ex, U_(cV[0]), U_(cV[1]), U_(cV[2]), U_(cV[3]));
          BAR_ARRIVE(B_T2, 256);
        } else {
          BAR_SYNC(B_T2, 256);
          const float4 u = lds4f(ex);
          stg_b64(mkp(xv ^ ((s & 1) * X_RING), HI(xc)), (pk(cV[0] + u.x, cV[1] + u.y) & ~1u) | (((s >> 1) + 1) & 1), pk(cV[2] + u.z, cV[3] + u.w));
        }
      }
      if (s == 63) break;
      {
        mbar_wait(obar, 0);
        const uint32_t woB = woA ^ 32;
        uint32_t wo[16][4];
#pragma unroll
        for (int i = 0; i < NW1; i++) ldsm4t(wo[i], ((i & 1) ? woB : woA) + (i >= WPA ? wo[(i + 16 - WPA) & 15][0] & dZ : 0) + (i >> 1) * 2048);
        xpre = xdesc(0);
        asm volatile("" : "+l"(xpre));
        uint64_t vpre = 0;
        if (VW) { vpre = mkdesc(__shfl_sync(~0u, 1024 + WVS + wg * NVS * 2048, 0), 16, 1024); asm volatile("" : "+l"(vpre)); }
        uint32_t p[4], pm;
        float sum[4] = {0, 0, 0, 0}, su2[4] = {0, 0, 0, 0};
#define PSL() do { ldsm4t(p, oA + (SC - OB)); asm volatile("ldmatrix.sync.aligned.m8n8.x1.trans.shared.b16 {%0},[%1];" : "=r"(pm) : "r"(oA + (SC - OB) + 512) : "memory"); } while (0)
#define PSM() do { const uint32_t one = 0x3f803f80u; mma16(sum, one, one, one, one, p[0], p[1]); mma16(su2, one, one, one, one, p[2], p[3]); mma8(sum, one, one, pm); } while (0)
        BAR_SYNC(B_S, 416);
        if (s < 62) {
          float acc[16];
          if (VW) {
            WG_FENCE();
            wgmma_rs_n32_z(acc, wV[0], xpre);
#pragma unroll
            for (int i = NVR + NH - 1; i > 0 && i > NVR + NH - VO; i--) wgmma_rs_n32(acc, i < NVR ? wV[i] : vS[i - NVR], xpre + (i >> 2) * 256 + (i & 3) * 2, 1);
#pragma unroll
            for (int i = NVR + NH; i < 16; i++) wgmma_ssT_n32(acc, vpre + (i - NVR) * 128, xpre + (i >> 2) * 256 + (i & 3) * 2, 1);
#pragma unroll
            for (int i = NVR + NH - VO; i > 0; i--) wgmma_rs_n32(acc, i < NVR ? wV[i] : vS[i - NVR], xpre + (i >> 2) * 256 + (i & 3) * 2, 1);
            WG_COMMIT();
          } else rs_issue(acc, wQ, s + 2, true, true);
          mbar_wait(sb + BARS + 24, (s + 1) & 1);
          WG_WAIT(0);
#pragma unroll
          for (int i = NW1; i < NWB; i++) ldsm4t(wo[i], ((i & 1) ? woB : woA) + (i >= NW1 + WPC ? wo[(i + 16 - WPC) & 15][0] & dZ : 0) + (i >> 1) * 2048);
          const uint32_t d = park_ptr();
          BAR_SYNC(B_V, 512);
          if (PSO == 1 || PSO == 3) PSL();
          if (PSO == 1) PSM();
          park(acc, 0, 2, d);
        } else {
#pragma unroll
          for (int i = NW1; i < NWB; i++) ldsm4t(wo[i], ((i & 1) ? woB : woA) + (i >> 1) * 2048);
          BAR_SYNC(B_V, 512);
          if (PSO == 1 || PSO == 3) PSL();
          if (PSO == 1) PSM();
        }
#pragma unroll
        for (int i = NWB; i < NWP; i++) ldsm4t(wo[i], ((i & 1) ? woB : woA) + (i >> 1) * 2048);
        float inv0, inv1;
        if (!ASM && (PSO == 0 || PSO == 4)) PSL();
        if (!ASM && (PSO == 0 || PSO == 3 || PSO == 4)) PSM();
        if (!ASM && PSO < 2) { inv0 = sum[0] + su2[0]; inv1 = sum[1] + su2[1]; }
        SCHED_FENCE(57);
        BAR_SYNC(B_O, 416);
        float c[2][4] = {{0, 0, 0, 0}, {0, 0, 0, 0}};
        uint32_t o[4][4], arD;
#pragma unroll
        for (int i = 0; i < 2; i++) ldsm4t(o[i], oA + i * 512);
        SCHED_FENCE(46);
        if (PSO > 2) { inv0 = sum[0] + su2[0]; inv1 = sum[1] + su2[1]; }
        if (!ASM && PSO != 2) {
          asm("rcp.approx.ftz.f32 %0,%0;" : "+f"(inv0));
          asm("rcp.approx.ftz.f32 %0,%0;" : "+f"(inv1));
        }
#pragma unroll
        for (int i = 0; i < 16; i++) {
          mma16(c[i & 1], wo[i][0], wo[i][1], wo[i][2], wo[i][3], o[i >> 2][i & 2], o[i >> 2][(i & 2) + 1]);
          if (i == 1) ldsm4t(o[2], oA + 1024);
          if (i == 7) { ldsm4t(o[3], oA + 1536); arD = lds1(tp + T_AR); }
          if (ASM && i == 8) {
            const uint2 u = lds2u((oA & 0xff000030u) / 2 + (oA & 0xff000000u) / 2 + 1024 + BARS + 192);
            asm("rcp.approx.ftz.f32 %0,%1;" : "=f"(inv0) : "f"(F_(u.x)));
            asm("rcp.approx.ftz.f32 %0,%1;" : "=f"(inv1) : "f"(F_(u.y)));
          }
          if (PSO == 2 && i == 8) PSL();
          if (PSO == 2 && i == 12) {
            PSM();
            asm("rcp.approx.ftz.f32 %0,%1;" : "=f"(inv0) : "f"(sum[0] + su2[0]));
            asm("rcp.approx.ftz.f32 %0,%1;" : "=f"(inv1) : "f"(sum[1] + su2[1]));
          }
          if (i + NWP < 16) ldsm4t(wo[(i + NWP) & 15], (((i + NWP) & 1) ? woB : woA) + ((i + NWP) >> 1) * 2048);
        }
        stsm4(arD, pk(c[0][0] * inv0, c[0][1] * inv1), pk(c[0][2] * inv0, c[0][3] * inv1), pk(c[1][0] * inv0, c[1][1] * inv1), pk(c[1][2] * inv0, c[1][3] * inv1));
      }
      const uint32_t d = park_ptr();
      BAR_SYNC(B_W, 384);
      if (s < 62) {
        vk_pass(s + 2, d, false);
        BAR_ARRIVE(B_P, 384); BAR_ARRIVE(B_X, 320);
        TS(10);
      } else {
        mA = lds1(tp + T_MEM);
      }
    }
  } else if (role == 3) {
    asm volatile("setmaxnreg.dec.sync.aligned.u32 24;");
    if (blockIdx.x >= 128) {
      if (threadIdx.x < 416) {
#pragma unroll 1
        for (int k = 0; k < 32; k++) {
          BAR_SYNC(B_W, 288);
          asm volatile("{.reg .pred p; elect.sync _|p, 0xffffffff; @p cp.async.bulk.tensor.3d.global.shared::cta.bulk_group [%0,{0,%1,%2}],[%3]; cp.async.bulk.commit_group;}"
                       ::"l"(&mp.hst), "r"((blockIdx.x & 1) * 16), "r"(k * 32 + (blockIdx.x & 2) * 8), "r"(sb + 152 * 1024 + (k & 1) * 32768) : "memory");
          if (k < 4 || (k & 3) == 3)
            asm volatile("{.reg .pred p; cp.async.bulk.wait_group 0; elect.sync _|p, 0xffffffff; @p st." HREL ".gpu.global.u32 [%0],%1;}" ::"l"((unsigned*)&g_hprog + (blockIdx.x & 3)), "r"(k + 1) : "memory");
          else BULK_WAIT_READ(0);
        }
        BAR_ARRIVE(B_O, 320);
      } else if (threadIdx.x < 448) {
        wait_h(HPW);
#pragma unroll 1
        for (int r0 = 0; r0 < 1024; r0 += 128) {
          if (r0 == HPR) BAR_ARRIVE(B_O, 320);
          if (threadIdx.x == 416) {
#pragma unroll 1
            for (int r = r0; r < r0 + 128; r += 32) {
#pragma unroll 1
              for (int c = 0; c < 4; c++) {
                tma2d_pf(&mp.wm, 2048 + (blockIdx.x & 3) * 1024 + c * 256, r);
                wait_until(clk(), HPS);
              }
            }
          }
          __syncwarp();
        }
      }
      return;
    }
    ROLE_VARS
    const uint32_t L16 = sb + (tid & 31) * 16;
    CLUSTER_SYNC();
    sts1(sb + PACE + 36, LO(xc) + h * 262144 + X_VM(0));
    auto vm_stage = [&](int s) {
      const uint32_t tag = ((s >> 1) + 1) & 1;
      const char* xm = mkp(lds1(sb + PACE + 36) + (s & 1) * X_RING + iw * XC + (l16 >> 1), HI(xc));
      uint2 m[4];
      CONSUME(LO(xm));
      BAR_SYNC(B_S2, 256);
      if (dZ2 > 1) { const uint32_t c = clk(); while (clk() - c < (uint32_t)dZ2) {} }
      int it = 0;
      while (true) {
#pragma unroll
        for (int i = 0; i < 4; i++) m[i] = ldg_b64(xm + (i >> 1) * 2048 + (i & 1) * 256);
        sts4(L16 + VN + iw * 512, m[0].x, m[0].y, m[1].x, m[1].y);
        sts4(L16 + VN + iw * 512 + 2048, m[2].x, m[2].y, m[3].x, m[3].y);
        if (!anybad(m[0].x, m[1].x, m[2].x, m[3].x, tag)) break;
        RP(2);
        if (++it > SPIN_LIMIT) __trap();
      }
      if (s < 63) BAR_ARRIVE(B_V, 512); else BAR_ARRIVE(B_V, 256);
    };
    if (iw == 0) {
      wait_h(1);
#pragma unroll 1
      for (int s = 0; s < 63; s++) {
        if (s) BAR_SYNC(B_R, 320); else BAR_SYNC(B_Q, 288);
        if (s < 62)
          asm volatile("{.reg .pred p; elect.sync _|p, 0xffffffff; @p mbarrier.arrive.expect_tx.shared.b64 _,[%2],32768;\n"
                       "@p cp.async.bulk.shared::cluster.global.mbarrier::complete_tx::bytes.L2::cache_hint [%0],[%1],32768,[%2],%3;}"
                       ::"r"(sb + XB), "l"(g_h + (s + 2) * 4096 + a * 2048), "r"(sb + BARS + 136), "l"(pol_stream()) : "memory");
        if (s >= 7) {
          const uint32_t zo = b * 160 + l16;
          if (l16 < 160) CONSUME(exch_b128((char*)g_ar + (zo >> 7) * 1024 + (zo & 127) + ((s + 1) & 7) * 128, 0, 0, 0, 0).x);
          __syncwarp();
        }
        if (s < 62) mbar_wait(sb + BARS + 136, (s + X1) & 1);
        BAR_ARRIVE(B_S, 416);
        vm_stage(s);
        BAR_ARRIVE(B_O, 416);
        BAR_SYNC(B_W, 384);
        FENCE_ASYNC_SMEM();
        asm volatile("{.reg .pred p; elect.sync _|p, 0xffffffff; @p cp.reduce.async.bulk.tensor.2d.global.shared::cta.add.bulk_group [%0,{%1,%2}],[%3];}"
                     ::"l"(&mp.ari), "r"((s & 7) * 64), "r"(j * 40), "r"(sb + ARO) : "memory");
        BULK_COMMIT();
        asm volatile("st.relaxed.gpu.global.u32 [%0],%1;" ::"l"(g_tm + (s & 1) * 128 + b), "r"(gtime()) : "memory");
        TS(3);
        if ((s & 1) && s < 61) wait_h((s + 3) >> 1);
        else if (!(s & 3) && s && b < 2 * GT)
          asm volatile("{.reg .pred p; elect.sync _|p, 0xffffffff; @p red.release.gpu.global.add.u32 [%0],1;}" ::"l"(g_oc + (s - 4) * 8) : "memory");
        BULK_WAIT_READ(0);
      }
      BAR_ARRIVE(B_R, 320);
    } else if (iw == 1) {
      const uint32_t pc = sb + MEM + (lane >> 2) * 640 + (lane & 3) * 144 + (lane & 12), pd = sb + MEM + (lane & 15) * 640 + 576 + (lane & 3) * 16 + (lane & 12);
      uint32_t T = 0, par = 0;
      int est = dA;
      mbar_wait_q(sb + BARS + 88, 0);
      wait_until(clk(), LD3);
#pragma unroll 1
      for (int c = 0; c < 4; c++)
        asm volatile("{.reg .pred p; elect.sync _|p, 0xffffffff; @p cp.async.bulk.prefetch.L2.global [%0], 8192;}" ::"l"((const char*)x + b * 8192 + c * 1048576) : "memory");
#pragma unroll 1
      for (int s = 0; s < 63; s++) {
        if (s) {
          const uint4 tm = ldg_rlx4((const char*)g_tm + ((s + 1) & 1) * 512 + l16);
          const int t0 = tm.x - T, t1 = tm.y - T, t2 = tm.z - T, t3 = tm.w - T;
          const int e = max(dF + (__reduce_add_sync(~0u, (t0 + t1) + (t2 + t3)) >> 7), dV + __reduce_max_sync(~0u, max(max(t0, t1), max(t2, t3))));
          if (s > 1) est += max(min(e >> (e > 0 ? 2 : 1), dP), -dX2);
          T += (s == 1 || e > dM ? e : 0) + est;
        }
        vm_stage(s);
        BAR_SYNC(B_W, 384);
        SCHED_FENCE(70);
        const uint32_t tW = gtime();
        if (s == 0) T = tW + 800;
        const uint32_t te = tW + min(max((int)(T - tW), dD), 2000);
        while ((int)(gtime() - te) < 0) {}
        TS(7);
        int it = 0;
        while (true) {
          ar_fetch(sb + MEM, &mp.ari, s & 7, a, sb + BARS + 112);
          mbar_wait(sb + BARS + 112, par);
          par ^= 1;
          const uint32_t n0 = lds1(pc), n1 = lds1(pc + 5120), n2 = lds1(pd);
          if (!__any_sync(~0u, (tagbad(n0, n1, 0x42004200) | (n2 ^ 0x42004200)) != 0)) break;
          RP(0);
          if (++it > SPIN_LIMIT) __trap();
        }
        BAR_ARRIVE(B_R, 320);
        TS(11);
        if (WPF && s == WPF)
          asm volatile("{.reg .pred p; elect.sync _|p, 0xffffffff; @p cp.async.bulk.prefetch.L2.global [%0], 8192;}" ::"l"((const char*)wo_g + GT * 131072 + b * 8192) : "memory");
      }
    } else {
#define V_LOAD(n) asm volatile("{.reg .pred p; elect.sync _|p, 0xffffffff; @p mbarrier.arrive.expect_tx.shared.b64 _,[%3],8192;\n" \
        "@p cp.async.bulk.tensor.5d.shared::cluster.global.mbarrier::complete_tx::bytes [%0+%4],[%1,{0,0,0,0,%2}],[%3];\n" \
        "@p cp.async.bulk.tensor.5d.shared::cluster.global.mbarrier::complete_tx::bytes [%0+%5],[%1,{0,0,0,1,%2}],[%3];}" \
        ::"r"(sb), "l"(&mp.vx), "r"(h * 32 + X_VRING(n) / 8192), "r"(sb + BARS + 8), "n"(VX0), "n"(VX1) : "memory")
      uint32_t src = L16 + PK + (iw & 1) * 2048;
#define qd (L16 + (lane >> 4) * 256 + QT + (iw & 1) * 1024)
#define vd (LO(xc) + h * 262144 + j * XC + (iw & 1) * 2048 + l16)
#define FINISH [&](int n, int m) { \
_Pragma("unroll") \
        for (int i = 1; i >= 0; i--) { \
          const uint32_t p = src + m * 4096 + i * 512; \
          uint4 u; \
            asm volatile("{.reg .b32 a<4>, b<4>, c<4>, d<4>;\n" \
              "ld.shared.v4.u32 {a0,a1,a2,a3},[%4]; ld.shared.v4.u32 {b0,b1,b2,b3},[%4+1024]; ld.shared.v4.u32 {c0,c1,c2,c3},[%4+12288];\n" \
              "add.rn.bf16x2 a0,a0,b0; add.rn.bf16x2 a1,a1,b1; add.rn.bf16x2 a2,a2,b2; add.rn.bf16x2 a3,a3,b3;\n" \
              "lop3.b32 d0,a0,%5,%4,0xea; ld.shared.v4.u32 {b0,b1,b2,b3},[d0+13312];\n" \
              "add.rn.bf16x2 a0,a0,c0; add.rn.bf16x2 a1,a1,c1; add.rn.bf16x2 a2,a2,c2; add.rn.bf16x2 a3,a3,c3;\n" \
              "add.rn.bf16x2 %0,a0,b0; add.rn.bf16x2 %1,a1,b1; add.rn.bf16x2 %2,a2,b2; add.rn.bf16x2 %3,a3,b3;}" \
              : "=r"(u.x), "=r"(u.y), "=r"(u.z), "=r"(u.w) : "r"(p), "r"(dZ) : "memory"); \
          if (m == (VW ? 0 : 2)) stg_b128(mkp(vd ^ X_VRING(n), HI(xc)) + i * 512, (u.x & ~1u) | X_VTAG(n), u.y, u.z, u.w); \
          else stsm4(qd + (n & 1) * 4096 + (m & 1) * 2048 + i * 256, u.x, u.z, u.y, u.w); \
          SCHED_FENCE(71 + m * 2 + i); \
        } \
      }
#pragma unroll 1
      for (int n = 0; n < 64; n++) {
        src = PIN(src);
        b = __shfl_sync(~0u, lds1(sb + PACE + 24), 0);
        const uint32_t L16 = src - PK - (iw & 1) * 2048;
        auto finish = FINISH;
        if (n < 2) BAR_SYNC(B_C, 320);
        if (n == 1) BAR_ARRIVE(B_T0, 320);
        mbar_wait(sb + BARS + 16, n & 1);
        finish(n, 0);
        __syncwarp();
        if (lane == 0 && n < 63) mbar_arrive_cl(mapa(sb, a ^ 1) + BARS + 24);
        BAR_SYNC(B_K, 320);
        mbar_wait(sb + BARS + 40, n & 1);
        finish(n, 2);
        BAR_SYNC(B_X, 320);
        mbar_wait(sb + BARS + 32, n & 1);
        finish(n, 1);
        BAR_SYNC(B_T, 64);
        if (lane == 0 && n < 63) {
          if (iw == 2) { mbar_expect(sb + BARS + 16, 4096); mbar_expect(sb + BARS + 32, 4096); mbar_expect(sb + BARS + 40, 4096); }
          mbar_arrive_cl(mapa(sb, a ^ 1) + BARS + 80);
        }
        __syncwarp();
        if (n) {
          vm_stage(n - 1);
          BAR_SYNC(B_W, 384);
        } else {
          if (X1) BAR_SYNC(B_H, 320); else BAR_SYNC(B_C, 320);
        }
        if (iw == 2) { wait_until(clk(), VDL); V_LOAD(n); }
      }
#undef qd
#undef vd
    }
    vm_stage(63);
  } else {
    asm volatile("setmaxnreg.dec.sync.aligned.u32 %0;" ::"n"(RA_));
    if (blockIdx.x >= 128) return;
    ROLE_VARS
    uint32_t L16 = __shfl_sync(~0u, sb + (tid & 31) * 16, tid & 31);
    CLUSTER_ARRIVE();
    if (tid == 256) {
      const int col = h * 128 + bb * 64;
      for (int c = 0; c < 12 + WIN; c++) {
        const uint32_t mb = sb + PACE + (c % WIN) * 8;
        if (c >= WIN) mbar_wait(mb, (c / WIN - 1) & 1);
        if (c == 7 + WIN) asm volatile("mbarrier.arrive.shared.b64 _,[%0];" ::"r"(wbar) : "memory");
        if (c >= 12) continue;
        if (c == 1) wait_until(clk(), LD1);
        mbar_expect(mb, 16384);
        if (c < 8) tma2d_s(sb + (c & 1) * XB + (c >> 1) * 16384, (c & 1) ? &mp.wk : &mp.wq, col, a * 512 + (c >> 1) * 128, mb);
        else
#pragma unroll 1
          for (int i = (c & 1) * 8; i < (c & 1) * 8 + 8; i++) {
            const int w = (c - 8) >> 1;
            tma2d_s(i < NVR ? sb + MEM + (w * NVR + i) * 2048 : sb + WVS + (w * NVS + i - NVR) * 2048, &mp.wv, col, a * 512 + w * 256 + i * 16, mb);
          }
      }
      asm volatile("mbarrier.arrive.shared.b64 _,[%0];" ::"r"(sb + BARS + 88) : "memory");
      PTT(61, 256);
      wait_until(clk(), LD2);
#pragma unroll 1
      for (int c = 0; c < 4; c++) tma2d_pf(&mp.wo, j * 256 + c * 64, h * 128);
    }
    __syncwarp();
    CLUSTER_WAIT();
#define pr (L16 + SC)
    {
      const int lim = j * 8 + iw * 2 - (lane & 7) - (lane & 8) * 2;
      const bool mk = L16 & 256;
      const int rw = lane >> 2;
      sts4(L16 + TA + iw * 512,
           W3P && iw == 3 ? 0 : iw != 2 ? L16 + KT + (iw & 1) * 256 + (lane >> 4) * 256 : sb + RK + (L16 & 0x80) * 2 + ((L16 >> 1) & 0x80) + (L16 & 0x70),
           L16 + QT + (lane >> 3) * 384, sb + SC + min(lane >> 3, 2) * 256 + (L16 & 0x70) + iw * 4, L16 + (lane >> 4) * 256 + QT + (iw >> 1) * 1024 + (iw & 1) * 256);
      const uint4 u = make_uint4(mk ? 0u : (lim < 0 ? 0xfc00u : 0u) | (lim < -1 ? 0xfc000000u : 0u),
           mk ? 0xfc00fc00u : (lim < 8 ? 0xfc00u : 0u) | (lim < 7 ? 0xfc000000u : 0u),
           ((h * 2 + (iw >> 1)) * 1024 + (j * 8 + rw) * 8 + (((iw & 1) * 4 + ((lane & 3) ^ (rw >> 1))) ^ rw)) * 16, sb + OT + iw * 512 + (L16 & 0x70) * 4 + (((L16 >> 3) ^ (L16 >> 1)) & 0x30));
      if (AT8) { const uint32_t t = sb + TA + 2048 + iw * 512 + lane * 8; sts1(t, u.x); sts1(t + 4, u.y); sts1(t + 256, u.z); sts1(t + 260, u.w); }
      else sts4(L16 + TA + 2048 + iw * 512, u.x, u.y, u.z, u.w);
    }
    {
      const uint32_t xh = LO(xc) + h * 262144, xs = xh + X_SC + iw * 1024 + min(lane, 16 + (lane & 7)) * 8;
      sts4(L16 + TA + 4096 + iw * 512, xh + X_SC + j * 256 + iw * 64 + lpub, xs, dS, iw != 2 ? 0 : U_(SCS));
      sts1(L16 + TA + 12 + iw * 512, xs + X_TOK + j * 4096);
      if (AT8) { const uint32_t t = sb + TA + 6144 + iw * 256 + lane * 8; sts1(t, xs + X_TOK + j * 4096); sts1(t + 4, lds1(L16 + TA + 8 + iw * 512)); }
    }
    uint32_t tA = L16 + TA + iw * 512;
#define tw (tA - L16 != TA + 1024)
#define w3_ (tA - L16 == TA + 1536)
#define XP_(lo) mkp(lo, HI(xc))
    auto publish = [&](char* d, const uint2& w) { stg_b64(d, w.x, w.y); };
    {
      const uint32_t xo = lds1(tA + 4096);
#pragma unroll 1
      for (int i = 0; i < 10; i++) stg_b64(XP_(xo + (i & 1) * X_RING + (i >> 1) * 4096), 0, 0);
    }
    BAR_SYNC(B_P, 384);
    for (int s = 0; s < 64; s++) {
      asm volatile("" : "+r"(L16), "+r"(tA));
      const uint32_t tag = ((s >> 1) + 1) & 1, ring = (s & 1) * X_RING;
      const uint4 t0 = lds4(tA);
      const uint4 tx = lds4(tA + 4096);
      const uint32_t xo = tx.x ^ ring, xs = tx.y ^ ring;
      const float gm = F_(tx.w);
      const uint32_t qA = t0.y + (ring >> 5);
      uint32_t c0;
      uint2 ts[4];
      uint4 v[4];
      uint32_t af[2][4], qt[4][4];
      {
        const uint32_t aA = t0.x + (tw ? ring >> 5 : 0);
        uint32_t ql[2][4], qr[2][4];
        uint2 pw_;
        float c[4] = {0, 0, 0, 0}, d[4] = {0, 0, 0, 0};
        if (s == PDS) asm volatile("griddepcontrol.launch_dependents;");
#pragma unroll
        for (int i = 0; i < 4; i++) ldsm4t_p(qt[i], qA + i * 128, t0.x);
        mbar_wait(sb + BARS + 8, s & 1);
        TS(4);
        BAR_SYNC(B_E, 256);
#define PACK(c) make_uint2(pkh(fmaf(c[2], gm, c[0] * SCS), fmaf(c[3], gm, c[1] * SCS), tag), pkh(c[2] * SCS, c[3] * SCS, tag))
        ldsm4t_p(ql[0], L16 + RQ, t0.x); ldsm4t_p(ql[1], L16 + RQ + 1024, t0.x); ldsm4t_p(af[0], aA, t0.x); ldsm4t_p(af[1], aA + 1024, t0.x);
        CONSUME(xo);
#define QSUM(t, i) addbf(addbf(ql[t][i], ql[t][i + 2]), addbf(qr[t][i], qr[t][i + 2]))
#define STAIL mma16(c, af[0][0], af[0][1], af[0][2], af[0][3], QSUM(0, 0), QSUM(0, 1)); mma16(d, af[1][0], af[1][1], af[1][2], af[1][3], QSUM(1, 0), QSUM(1, 1));
        if (tw) {
          mbar_wait(sb + BARS, s & 1);
          TS(8);
          ldsm4t_p(qr[0], L16 + RQ + 512, t0.x); ldsm4t_p(qr[1], L16 + RQ + 1536, t0.x);
          STAIL
          pw_ = make_uint2(pkh(c[0] + d[0], c[1] + d[1], tag), pkh(c[2] + d[2], c[3] + d[3], tag));
        } else {
          uint32_t ar[2][4];
          mbar_wait(sb + BARS, s & 1);
          ldsm4t(qr[0], L16 + RQ + 512); ldsm4t(qr[1], L16 + RQ + 1536); ldsm4t(ar[0], aA + 512); ldsm4t(ar[1], aA + 1536);
#pragma unroll
          for (int i = 0; i < 8; i++) af[i >> 2][i & 3] = addbf(af[i >> 2][i & 3], ar[i >> 2][i & 3]);
          STAIL
          pw_.x = pw_.y = pkh((c[0] + c[2]) + (d[0] + d[2]), (c[1] + c[3]) + (d[1] + d[3]), tag);
        }
        publish(XP_(xo), pw_);
        c0 = clk() + tx.z;
        TS(1);
      }
      uint2 r[4];
      {
        float e[4][4];
#pragma unroll
        for (int i = 0; i < 4; i++) e[i][0] = e[i][1] = e[i][2] = e[i][3] = 0.f;
        {
#pragma unroll
          for (int i = 0; i < 4; i++) mma16(e[i], af[0][0], af[0][1], af[0][2], af[0][3], qt[i][0], qt[i][1]);
#pragma unroll
          for (int i = 0; i < 4; i++) mma16(e[i], af[1][0], af[1][1], af[1][2], af[1][3], qt[i][2], qt[i][3]);
        }
        SCHED_FENCE(55);
        if (VE) {
          v[0] = lds4(tA + (VX0 - TA)); v[1] = lds4(tA + (VX0 - TA) + 2048); v[2] = lds4(tA + (VX1 - TA)); v[3] = lds4(tA + (VX1 - TA) + 2048);
          if (VE == 2) CONSUME(v[0].x & v[1].x & v[2].x & v[3].x);
        }
        if (s < 63) BAR_ARRIVE(B_S, 416);
        SCHED_FENCE(58);
        if (!VE) { v[0] = lds4(tA + (VX0 - TA)); v[1] = lds4(tA + (VX0 - TA) + 2048); v[2] = lds4(tA + (VX1 - TA)); v[3] = lds4(tA + (VX1 - TA) + 2048); }
#pragma unroll
        for (int i = 0; i < 4; i++) ts[i] = PACK(e[i]);
        while ((int)(clk() - c0) < 0) {}
        TS(5);
#pragma unroll
        for (int u = 0; u < 4; u++) r[u] = ldg_b64(XP_(xs) + u * 256);
        BAR_ARRIVE(B_S2, 256);
      }
      const uint32_t fn = (L16 & 256) ? 0xfc00fc00u : 0u;
      float4 e = softmax2<false>(r, 0, fn);
      const bool vbad = anybad(v[0].x, v[1].x, v[2].x, v[3].x, X_VTAG(s));
      if (BADS(r)) {
        int it = 0;
        if (s > 8) sts1(tA + 4096 + 8, min(lds1(tA + 4096 + 8) + dX, 500));
        do {
          RP(1);
          if (++it > SPIN_LIMIT) __trap();
#pragma unroll
          for (int u = 0; u < 4; u++) r[u] = ldg_b64(XP_(xs) + u * 256);
        } while (BADS(r));
        e = softmax2<false>(r, 0, fn);
      }
      sts1(t0.z, pk(e.x, e.y)); sts1(t0.z + 128, pk(e.z, e.w));
#pragma unroll
      for (int i = 0; i < 4; i++) publish(XP_(xo) + X_TOK + i * 4096, ts[i]);
      TS(6);
      if (s < 63) BAR_SYNC(B_V, 512); else BAR_SYNC(B_V, 256);
      uint32_t O[4];
      uint4 vn[2];
      {
        uint32_t p[4], pm;
        ldsm4t(p, pr);
        vn[0] = lds4(tA + (VN - TA)); vn[1] = lds4(tA + (VN - TA) + 2048);
        asm volatile("ldmatrix.sync.aligned.m8n8.x1.trans.shared.b16 {%0},[%1];" : "=r"(pm) : "r"(pr + 512) : "memory");
        pv_mem(p, pm, v, vn, O, sb + BARS + 192 + ((L16 >> 1) & 24), L16);
        if (vbad) {
          int it = 0;
          do {
            if (++it > SPIN_LIMIT) __trap();
#pragma unroll
            for (int u = 0; u < 4; u++) v[u] = ldg_b128(XP_((LO(xc) + (lds1(sb + PACE + 24) >> 2) * 262144 + ((tA - L16 - TA) >> 9) * XC + l16) ^ X_VRING(s)) + X_VX(u));
          } while (anybad(v[0].x, v[1].x, v[2].x, v[3].x, X_VTAG(s)));
          pv_mem(p, pm, v, vn, O, sb + BARS + 192 + ((L16 >> 1) & 24), L16);
        }
      }
      stsm4(tA + (OB - TA), O[0], O[1], O[2], O[3]);
      if (s < 63) BAR_ARRIVE(B_O, 416);
      TS(2);
      c0 = clk() + (LG && s == 63 ? 0 : dG);
      SCHED_FENCE(60);
      if (tA == sb + TA) mbar_expect(sb + BARS, 2048);
      const uint32_t vs[4] = {addbf(vn[0].x, vn[0].z), addbf(vn[0].y, vn[0].w), addbf(vn[1].x, vn[1].z), addbf(vn[1].y, vn[1].w)};
      {
        const uint2 t3 = AT8 ? lds2u(sb + TA + 6144 + ((tA - sb - TA) >> 1)) : make_uint2(lds1(tA + 12), lds1(tA + 8));
        const char* xt = XP_(t3.x ^ ring);
        const uint2 t1 = lds2u(AT8 ? tA - (l16 >> 1) + 2048 : tA + 2048);
        const uint32_t pw = t3.y;
        uint2 rt[4];
        CONSUME(LO(xt) ^ t1.x ^ pw);
        while ((int)(clk() - c0) < 0) {}
        int it = 0;
        do {
          if (++it > SPIN_LIMIT) __trap();
#pragma unroll
          for (int u = 0; u < 4; u++) rt[u] = ldg_b64(xt + u * 256);
        } while (BADS(rt));
        const float4 et = softmax2<true>(rt, t1.x, t1.y);
        sts1(pw + SCT, pk(et.x, et.y)); sts1(pw + SCT + 128, pk(et.z, et.w));
      }
      s = PIN(s);
      BAR_SYNC(B_SC, 128);
      {
        uint32_t Ot[4], p[4], pm;
        const uint2 t2 = lds2u(AT8 ? tA - (l16 >> 1) + 2048 + 256 : tA + 2048 + 8);
        ldsm4t(p, pr + SCT);
        asm volatile("ldmatrix.sync.aligned.m8n8.x1.trans.shared.b16 {%0},[%1];" : "=r"(pm) : "r"(pr + SCT + 512) : "memory");
        char* od = (char*)g_O + ((s >> 2) * 1048576 + (s & 3) * 4096) + t2.x;
        CONSUME(LO(od) ^ HI(od) ^ pm ^ p[3]);
        TS(9);
        if (s < 62) BAR_SYNC(B_P, 384);
        pv_tok(p, pm, v, vs, Ot);
        asm volatile("stmatrix.sync.aligned.m8n8.x4.trans.shared.b16 [%0],{%1,%2,%3,%4};" ::"r"(t2.y), "r"(Ot[0]), "r"(Ot[1]), "r"(Ot[2]), "r"(Ot[3]) : "memory");
        __syncwarp();
        *(uint4*)od = lds4(tA + (OT - TA));
      }
    }
  }
  PH(5);
  if (threadIdx.x == 0) FT(40);
  PDUMP();
}
#undef wg
#undef iw
#undef h
#undef j
#undef a
#undef bb
#undef oi
#undef owner
#undef pr
#undef PIN
#undef XP_
#undef tw
#undef w3_
#undef lane
#undef l16
#undef lrow
#undef lpub

namespace ffn {
constexpr uint32_t STG = 196608;
constexpr uint32_t PRM = 229376;
constexpr uint32_t BARS = PRM + 2176;
constexpr uint32_t SMEM = BARS + 16 * 8;
}
#define UBASE (g_O + rb * 65536)
struct FfnMaps { CUtensorMap wo, w1a, w1b, w2, xp, out, x, xps, wo4; int zero[16]; };

template <int N>
__device__ __forceinline__ void wg_ss(float* d, uint64_t a, uint64_t b, int sd) {
  if (N == 128) wgmma_ss_n128(d, a, b, sd);
  if (N == 192) wgmma_ss_n192(d, a, b, sd);
  if (N == 256) wgmma_ss_n256(d, a, b, sd);
}
template <int N>
__device__ __forceinline__ void ffn_issue(float* acc, uint32_t full, uint32_t par, uint32_t a, uint32_t b, bool first) {
  mbar_wait(full, par);
  const uint64_t da = mkdesc(0, 0, 1024) | a, db = mkdesc(0, 0, 1024) | b;
  WG_FENCE();
#pragma unroll
  for (int j = 0; j < 4; j++) wg_ss<N>(acc, da + j * 2, db + j * 128, !first || j);
  WG_COMMIT();
}
__device__ __forceinline__ void ffn_release(uint32_t leader, uint32_t e) {
  asm volatile("{.reg .pred p; setp.ne.u32 p,%0,0; @p mbarrier.arrive.shared.b64 _,[%1];}" ::"r"(leader), "r"(e) : "memory");
}
__device__ __forceinline__ void ffn_done(unsigned* cnt) {
  asm volatile("{.reg .pred p; cp.async.bulk.wait_group 0; elect.sync _|p, 0xffffffff; @p red.relaxed.gpu.global.add.u32 [%0],1;}" ::"l"(cnt) : "memory");
}
template <int N>
__device__ __forceinline__ void acc_fence(float* d) {
#pragma unroll
  for (int i = 0; i < N; i++) asm volatile("" : "+f"(d[i])::"memory");
}
__device__ __forceinline__ float gelu_h(float hx) {
  float t;
  asm("tanh.approx.f32 %0,%1;" : "=f"(t) : "f"(hx * fmaf(hx * hx, 8 * 0.0356774081f, 2 * 0.7978845608f)));
  return fmaf(hx, t, hx);
}
template <int N>
__device__ __forceinline__ void ffn_gelu(uint32_t (&u)[N], int i, const uint2& b, uint32_t stw, uint32_t z) {
  uint32_t o[4];
#pragma unroll
  for (int e = 0; e < 4; e++) {
    uint32_t h;
    asm("fma.rn.bf16x2 %0,%1,%2,%3;" : "=r"(h) : "r"(u[i * 4 + e]), "r"(0x3f003f00), "r"(e < 2 ? b.x : b.y));
    o[e] = pk(gelu_h(blo(h)), gelu_h(bhi(h)));
#pragma unroll
    for (int j = i * 4 + e; j < N - 16; j += 16) u[j] = u[j + 16] ^ z;
  }
  stsm4(stw ^ (i * 32), o[0], o[1], o[2], o[3]);
}
__device__ __forceinline__ void ffn_store(uint32_t stg, const uint4* dst) {
  FENCE_ASYNC_SMEM();
  __syncwarp();
  asm volatile("{.reg .pred p; elect.sync _|p, 0xffffffff; @p cp.async.bulk.global.shared::cta.bulk_group [%0],[%1],2048; cp.async.bulk.commit_group;\n"
               "cp.async.bulk.wait_group.read 1;}" ::"l"(dst), "r"(stg) : "memory");
  __syncwarp();
}
__device__ __forceinline__ uint32_t halfbf(uint32_t v) { return pk(0.5f * blo(v), 0.5f * bhi(v)); }

__device__ __forceinline__ void ffn_spare(const FfnMaps& mp, uint32_t sb, int cb, const char* x) {
  using namespace ffn;
  const int tid = threadIdx.x, lane = tid & 31, wid = __shfl_sync(~0u, tid >> 5, 0);
  const uint32_t full = sb + BARS, emp = full + 48, xbar = full + 104, XA = 147456;
  if (tid < 128) sts1(sb + PRM + (tid >> 4) * 64 + (tid & 3) * 16 + ((tid >> 2) & 3) * 4, pk(__ldcg(g_mod + 2048 + cb * 256 + tid * 2), __ldcg(g_mod + 2048 + cb * 256 + tid * 2 + 1)));
  __syncthreads();
  if (wid == 8) {
    int st = 0; uint32_t ph = 1;
#pragma unroll 1
    for (int rb = 0; rb < 16; rb++) {
#pragma unroll 1
      for (int i = rb ? 16 : 0; i < (rb < 15 ? 32 : 16); i++)
        asm volatile("prefetch.global.L2 [%0];" ::"l"(x + (rb * 128 + i * 8 + (lane >> 2)) * 2048 + cb * 512 + (lane & 3) * 128) : "memory");
      if (rb < 15) {
        int it = 0;
        while (ld_acq(g_oc + rb * 32) < 2 * GT) { __nanosleep(500); if (++it > SPIN_LIMIT) __trap(); }
      } else asm volatile("griddepcontrol.wait;" ::: "memory");
      FENCE_ASYNC_G();
#pragma unroll 1
      for (int k = 0; k < GT; k++) {
        mbar_wait_q(emp + st * 8, ph);
        e_expect_tma3d(sb + st * 49152 + 16384, &mp.wo4, k * 64, cb * 4, full + st * 8, 49152);
        e_bulk_ld(sb + st * 49152, g_O + rb * 65536 + k * 1024, 16384, full + st * 8);
        if (++st == 3) { st = 0; ph ^= 1; }
      }
    }
  } else if (wid < 8) {
    const int wg = wid >> 2, row0 = wid * 16;
    const uint32_t stg = sb + row0 * 128, stw = stg + (lane & 15) * 128 + (((lane >> 4) ^ (lane & 7)) << 4), prm = sb + PRM + (lane & 3) * 16;
    const uint32_t aw = (uint32_t)mkdesc(1024 + wg * 8192, 16, 0), leader = (tid & 127) == 0;
    constexpr uint32_t bw = (1024 + 16384) / 16 + (8192 / 16 << 16);
    int st = 0, prev = 0; uint32_t ph = 0;
#pragma unroll 1
    for (int rb = 0; rb < 16; rb++) {
      float acc[128];
      if (tid == 0) FT(44 + rb);
#pragma unroll 1
      for (int k = 0; k < GT; k++) {
        ffn_issue<256>(acc, full + st * 8, ph, aw + st * 3072, bw + st * 3072, k == 0);
        if (k == 2) {
          if (rb) ffn_done(g_oc + 480 + rb * 32 + cb);
          BAR_SYNC(1, 256);
          if (tid == 0) {
            mbar_expect(xbar, 65536);
            for (int i = 0; i < 4; i++) tma2d(sb + (i & 2 ? STG : XA) + (i & 1) * 16384, &mp.x, cb * 256 + i * 64, rb * 128, xbar);
          }
          __syncwarp();
        }
        WG_WAIT(1);
        ffn_release(leader && k, emp + prev * 8);
        prev = st;
        if (++st == 3) { st = 0; ph ^= 1; }
      }
      WG_WAIT(0);
      ffn_release(leader, emp + prev * 8);
      acc_fence<128>(acc);
      mbar_wait(xbar, rb & 1);
      uint4 pa, pn = lds4(prm);
      uint32_t xn[2][4];
#define XAD(j) ((stw ^ (((j) & 3) * 32)) + ((j) & 8 ? STG : XA) + ((j) & 4) * 4096)
      ldsm4(xn[0], XAD(0)); ldsm4(xn[1], XAD(1));
#pragma unroll
      for (int j = 0; j < 16; j++) {
        const uint32_t a = XAD(j), xv[4] = {xn[j & 1][0], xn[j & 1][1], xn[j & 1][2], xn[j & 1][3]};
        uint32_t o[4];
        if (j < 14) ldsm4(xn[j & 1], XAD(j + 2));
        if (!(j & 1)) { pa = pn; if (j < 14) pn = lds4(prm + ((j >> 1) + 1) * 64); }
#pragma unroll
        for (int e = 0; e < 4; e++) {
          const uint32_t g = (j & 1) ? (e < 2 ? pa.z : pa.w) : (e < 2 ? pa.x : pa.y);
          o[e] = pk(fmaf(blo(g), acc[j * 8 + e * 2], blo(xv[e])), fmaf(bhi(g), acc[j * 8 + e * 2 + 1], bhi(xv[e])));
        }
        stsm4(a, o[0], o[1], o[2], o[3]);
      }
      FENCE_ASYNC_SMEM();
      __syncwarp();
#pragma unroll 1
      for (int i = 0; i < 4; i++)
        asm volatile("{.reg .pred p; elect.sync _|p, 0xffffffff; @p cp.async.bulk.tensor.2d.global.shared::cta.bulk_group [%0,{%1,%2}],[%3];}"
                     ::"l"(&mp.xps), "r"(cb * 256 + i * 64), "r"(rb * 128 + row0), "r"(stg + (i & 2 ? STG : XA) + (i & 1) * 16384) : "memory");
      BULK_COMMIT();
    }
    ffn_done(g_oc + 512 + 15 * 32 + cb);
  }
  __syncthreads();
}

#define SL(st) (GT % 6 == 0 ? (st) : (st) + GT % 6 - ((st) >= 6 - GT % 6 ? 6 : 0))
__global__ void __launch_bounds__(384, 1)
k_ffn(const __grid_constant__ FfnMaps mp, const bf16* __restrict__ b1, const bf16* __restrict__ b2, const char* x) {
  using namespace ffn;
  extern __shared__ __align__(1024) char smem[];
  const uint32_t sb = (uint32_t)__cvta_generic_to_shared(smem);
  if ((sb & 0x3FFFF) != 1024) __trap();
  const int tid = threadIdx.x, lane = tid & 31, wg = __shfl_sync(~0u, tid >> 7, 0);
  int tile = ((int)blockIdx.x + 128) % 132;
  uint4 hs = ldg_rlx4(g_hsm);
  if (TMP && tid == 256) asm volatile("prefetch.tensormap [%0];" ::"l"(&mp.wo) : "memory");
  const uint32_t full = sb + BARS, emp = full + 48, xbar = full + 96, rdy = full + 96;
  if (tid == 256) {
#pragma unroll
    for (int i = 0; i < 6; i++) mbar_init(full + i * 8, 1);
    FENCE_ASYNC_SMEM();
  } else if (tid == 288) {
#pragma unroll
    for (int i = 0; i < 6; i++) mbar_init(emp + i * 8, 2);
  } else if (tid == 320) {
    mbar_init(xbar, 2);
#pragma unroll
    for (int i = 1; i < 4; i++) mbar_init(rdy + i * 8, 1);
    FENCE_ASYNC_SMEM();
  }
  __syncthreads();
  {
    uint32_t sm, nsm;
    asm volatile("mov.u32 %0,%%smid; mov.u32 %1,%%nsmid;" : "=r"(sm), "=r"(nsm));
    const uint32_t t = sm >> 1, u = ((t - 32) * 37) >> 8;
    const uint32_t g = t < 32 ? t & 7 : t < 60 ? t - 31 - u * 7 : 0, i = (t < 32 ? t >> 3 : t < 60 ? 4 + u : t - 58) * 2 + (sm & 1);
    const uint32_t m = ((g >> 1) * 4 + (i & 3)) * 8 + (g & 1) * 4 + (i >> 2);
    const bool usual = ((hs.x & hs.y & hs.z & hs.w) >> 2) == 30 && ((hs.x | hs.y | hs.z | hs.w) >> 2) == 30;
    if (nsm == 132)
      tile = sm == hs.x ? 128 : sm == hs.y ? 129 : sm == hs.z ? 130 : sm == hs.w ? 131 : usual ? m : sm - (hs.x < sm) - (hs.y < sm) - (hs.z < sm) - (hs.w < sm);
    tile = __shfl_sync(~0u, tile, 0);
  }
  if (tile >= 128) {
    ffn_spare(mp, sb, tile & 3, x);
    if (tid == 0) wait_cnt(&g_fcnt, 128);
    return;
  }
  const int rb = tile >> 3, nb = tile & 7;
  if (tid == 256) FT(34);
  const int wid = __shfl_sync(~0u, tid >> 5, 0);
  if (wid == 8) {
#pragma unroll
    for (int k = 0; k < 6; k++) { if (k) wait_until(clk(), 200); e_expect_tma3d<true>(sb + SL(k) * 32768 + 16384, &mp.wo, (GT + k) * 64, nb * 2, full + k * 8, 32768); }
    if (lane == 0) FT(36);
  } else if (wid == 9) {
    asm volatile("griddepcontrol.wait;" ::: "memory");
    if (lane == 0) FT(35);
    FENCE_ASYNC_G();
#pragma unroll
    for (int k = 0; k < 6; k++) { if (k) wait_until(clk(), 200); e_bulk_ld<true>(sb + SL(k) * 32768, g_O + rb * 65536 + (GT + k) * 1024, 16384, full + k * 8); }
    if (lane == 0) FT(2);
  } else if (tid == 320) {
    asm volatile("red.relaxed.gpu.global.add.u32 [%0],1;" ::"l"(&g_fcnt) : "memory");
  }
  unsigned* cnt = g_cnt + rb * 128;
  if (wg == 2) {
    asm volatile("setmaxnreg.dec.sync.aligned.u32 40;");
    const int pw = __shfl_sync(~0u, (tid >> 5) & 3, 0);
    uint32_t me = emp, mp_ = 0, st = 0;
    auto wait1 = [&]() { mbar_wait_q(me, mp_); me += 8; if (me == emp + 48) { me = emp; mp_ ^= 1; } };
#define NEXTS() do { if (++st == 6) st = 0; } while (0)
#define KT2(k) ((k) < 2 ? nb * 2 + (k) : (k) >= 16 ? (k) - 16 : (k) - 2 < nb * 2 ? (k) - 2 : (k))
#define KT3(k) (((k) & 7) * 7 + ((k) >> 3))
    if (pw == 0) {
#pragma unroll 1
      for (int k = GT + 6; k < 64; k++) {
        wait1();
        e_expect_tma3d<true>(sb + SL(st) * 32768 + 16384, &mp.wo, k * 64, nb * 2, full + st * 8, 32768);
        NEXTS();
      }
      wait1(); wait1(); wait1();
#pragma unroll 1
      for (int k = 0; k < 32; k++) {
        const int kt = KT2(k);
        if (k != 3) wait1();
        e_expect_tma3d<true>(sb + (k & 3) * 49152 + 16384, k < 16 ? &mp.w1a : &mp.w1b, kt * 64, nb * 7 + (k >> 4) * 4, full + st * 8, k < 2 ? 32768 : k < 16 ? 49152 : 40960);
        NEXTS();
      }
#pragma unroll 1
      for (int k = 0; k < 56; k++) {
        if (k != 2 && k != 5) wait1();
        e_expect_tma3d<true>(sb + SL(st) * 32768 + 16384, &mp.w2, KT3(k) * 64, nb * 2, full + st * 8, 32768);
        NEXTS();
      }
    } else if (pw == 1) {
      const uint4* A = g_O + rb * 65536;
#pragma unroll 1
      for (int k = GT + 6; k < 64; k++) {
        wait1();
        e_bulk_ld<true>(sb + SL(st) * 32768, A + k * 1024, 16384, full + st * 8);
        NEXTS();
      }
#pragma unroll 1
      for (int k = 0; k < 6; k++) wait1();
      wait_cnt(cnt, 64);
      if (lane == 0) FT(29);
      FENCE_ASYNC_G();
      st = (66 - GT) % 6;
      A = g_h2 + rb * 16384;
#pragma unroll 1
      for (int k = 2; k < 32; k++) {
        const int kt = KT2(k);
        if (k > 3) wait1();
        if (k == 3) wait_until(clk(), 250);
        e_bulk_ld(sb + (k & 3) * 49152, A + kt * 1024, 16384, full + st * 8);
        NEXTS();
      }
      A = UBASE;
#pragma unroll 1
      for (int k = 0; k < 56; k++) {
        if ((k & 15) == 0 && k < 48) { mbar_wait_q(rdy + 8 + (k >> 1), 0); FENCE_ASYNC_G(); }
        if (k != 2 && k != 5) wait1();
        e_bulk_ld<true>(sb + SL(st) * 32768, A + KT3(k) * 1024, 16384, full + st * 8);
        NEXTS();
      }
    } else if (pw == 2) {
      asm volatile("griddepcontrol.wait;" ::: "memory");
      if (lane < 16) g_modp[tile * 16 + lane] = make_uint4(0, 0, 0, 0);
      if (lane == 16 && tile == 0) g_hprog = make_uint4(0, 0, 0, 0);
      __nanosleep(2000);
      if (lane < 5) asm volatile("prefetch.tensormap [%0];" ::"l"(&mp.w1a + lane) : "memory");
      int it = 0;
      while (ld_acq(g_oc + 512 + rb * 32 + (nb >> 1)) < 8) { __nanosleep(200); if (++it > SPIN_LIMIT) __trap(); }
      FENCE_ASYNC_G();
#pragma unroll
      for (int i = 0; i < 8; i++) asm volatile("prefetch.global.L2 [%0];" ::"l"((const char*)g_xp + (rb * 128 + i * 16 + (lane >> 1)) * 2048 + nb * 256 + (lane & 1) * 128) : "memory");
      if (!it) __nanosleep(1500);
      if (lane == 0) {
        mbar_expect(xbar, 32768);
        tma2d(sb + STG, &mp.xp, nb * 128, rb * 128, xbar);
        tma2d(sb + STG + 16384, &mp.xp, nb * 128 + 64, rb * 128, xbar);
      }
    } else {
      const uint32_t prm = sb + PRM;
      const uint2 v2 = ((const uint2*)(b2 + nb * 128))[lane];
      auto put = [&](uint32_t at, uint32_t u, uint32_t v) {
        const uint32_t a = prm + at + (lane >> 3) * 64 + (lane & 1) * 32 + ((lane >> 1) & 3) * 4;
        sts1(a, u); sts1(a + 16, v);
      };
      put(1024, v2.x, v2.y);
#pragma unroll
      for (int i = 0; i < 7; i++) sts1(prm + 1280 + i * 128 + (lane & 3) * 32 + (lane >> 2) * 4, halfbf(((const uint32_t*)(b1 + nb * 448))[i * 32 + lane]));
      const float4* md = (const float4*)(g_mod + nb * 128) + lane;
      const float4 ga = __ldcg(md + 512), sbv = __ldcg(md + 768), cb = __ldcg(md + 1024), gb = __ldcg(md + 1280);
      put(0, pk(ga.x, ga.y), pk(ga.z, ga.w));
      put(256, pk(1.f + cb.x, 1.f + cb.y), pk(1.f + cb.z, 1.f + cb.w));
      put(512, pk(sbv.x, sbv.y), pk(sbv.z, sbv.w));
      put(768, pk(gb.x, gb.y), pk(gb.z, gb.w));
      __syncwarp();
      if (lane == 0) {
        asm volatile("mbarrier.arrive.shared.b64 _,[%0];" ::"r"(xbar) : "memory");
#pragma unroll 1
        for (int i = 1; i < 4; i++) {
          int it = 0;
          while (ld_acq(cnt + i * 32) < 64) { __nanosleep(200); if (++it > SPIN_LIMIT) __trap(); }
          asm volatile("mbarrier.arrive.shared.b64 _,[%0];" ::"r"(rdy + i * 8) : "memory");
        }
      }
    }
  } else {
    const int w = __shfl_sync(~0u, (tid >> 5) & 3, 0), q = lane & 3;
    const uint32_t leader = (tid & 127) == 0;
    const uint32_t prm = sb + PRM + q * 16;
#define PRM2(v, a, b, at) if (!(j & 1)) v = lds4(prm + (at) + (j >> 1) * 64); const uint32_t a = (j & 1) ? v.z : v.x, b = (j & 1) ? v.w : v.y;
    const int row0 = wg * 64 + w * 16;
    const uint32_t stg = sb + STG + row0 * 128;
    const uint32_t stw = stg + (lane & 15) * 128 + (((lane >> 4) ^ (lane & 7)) << 4);
    const uint32_t aw = (uint32_t)mkdesc(1024 + wg * 8192, 16, 0);
    constexpr uint32_t bw = (1024 + 16384) / 16 + (8192 / 16 << 16);
    uint32_t x1[32];
    {
      float acc[64];
      int st = 0, prev = 0; uint32_t ph = 0;
#pragma unroll 1
      for (int k = 0; k < 64 - GT; k++) {
        ffn_issue<128>(acc, full + st * 8, ph, aw + SL(st) * 2048, bw + SL(st) * 2048, k == 0);
        if (tid == 0 && (k & 7) == 0) FT(3 + (k >> 3));
        if (tid == 0 && k > 0 && k < 8) FT(19 + k);
        WG_WAIT(1);
        ffn_release(leader && k, emp + prev * 8);
        prev = st;
        if (++st == 6) { st = 0; ph ^= 1; }
      }
      WG_WAIT(0);
      ffn_release(leader, emp + prev * 8);
      acc_fence<64>(acc);
      asm volatile("setmaxnreg.inc.sync.aligned.u32 232;");
      PH(7); if (tid == 0) { FT(11); FC(38); }
      mbar_wait(xbar, 0);
      float s0 = 0, s1 = 0, q0 = 0, q1 = 0;
      uint4 pa;
#pragma unroll
      for (int j = 0; j < 8; j++) {
        uint32_t xv[4];
        ldsm4(xv, (stw ^ ((j & 3) * 32)) + (j >> 2) * 16384);
        PRM2(pa, g0, g1, 0)
        float* d = acc + j * 8;
#pragma unroll
        for (int e = 0; e < 4; e++) {
          const uint32_t g = e < 2 ? g0 : g1;
          x1[j * 4 + e] = pk(fmaf(blo(g), d[e * 2], blo(xv[e])), fmaf(bhi(g), d[e * 2 + 1], bhi(xv[e])));
          d[e * 2] = blo(x1[j * 4 + e]); d[e * 2 + 1] = bhi(x1[j * 4 + e]);
        }
        s0 += (d[0] + d[1]) + (d[4] + d[5]);
        s1 += (d[2] + d[3]) + (d[6] + d[7]);
      }
      s0 += __shfl_xor_sync(~0u, s0, 1); s1 += __shfl_xor_sync(~0u, s1, 1);
      s0 += __shfl_xor_sync(~0u, s0, 2); s1 += __shfl_xor_sync(~0u, s1, 2);
      s0 *= 1.f / 128; s1 *= 1.f / 128;
#pragma unroll
      for (int j = 0; j < 16; j++) {
        float* d = acc + j * 4;
        d[0] -= s0; d[1] -= s0; d[2] -= s1; d[3] -= s1;
        q0 += d[0] * d[0] + d[1] * d[1]; q1 += d[2] * d[2] + d[3] * d[3];
      }
      q0 += __shfl_xor_sync(~0u, q0, 1); q1 += __shfl_xor_sync(~0u, q1, 1);
      q0 += __shfl_xor_sync(~0u, q0, 2); q1 += __shfl_xor_sync(~0u, q1, 2);
      uint4* sp = g_stat + (rb * 128 + row0) * 4 + (lane >> 2);
      if (q == 0) stg_b128(sp + nb * 8, U_(s0), min(U_(q0), 0xfffffffeu), U_(s1), U_(q1));
      if (tid == 0) FT(12);
#pragma unroll
      for (int j = 0; j < 8; j++) {
        PRM2(pa, c0, c1, 256)
        float* d = acc + j * 8;
        d[0] *= blo(c0); d[1] *= bhi(c0); d[2] *= blo(c0); d[3] *= bhi(c0);
        d[4] *= blo(c1); d[5] *= bhi(c1); d[6] *= blo(c1); d[7] *= bhi(c1);
      }
      acc_fence<64>(acc);
      uint4 r0, r1;
      int it = 0;
      while (true) {
        r0 = ldg_b128(sp + q * 16); r1 = ldg_b128(sp + q * 16 + 8);
        if (__all_sync(~0u, r0.y != ~0u && r1.y != ~0u)) break;
        if (++it > SPIN_LIMIT) __trap();
      }
      if (tid == 0) FT(13);
      float m0 = F_(r0.x) + F_(r1.x), m1 = F_(r0.z) + F_(r1.z);
      m0 += __shfl_xor_sync(~0u, m0, 1); m1 += __shfl_xor_sync(~0u, m1, 1);
      m0 += __shfl_xor_sync(~0u, m0, 2); m1 += __shfl_xor_sync(~0u, m1, 2);
      m0 *= 0.125f; m1 *= 0.125f;
      float a = F_(r0.x) - m0, b = F_(r1.x) - m0, c = F_(r0.z) - m1, d = F_(r1.z) - m1;
      float v0 = F_(r0.y) + F_(r1.y) + 128.f * (a * a + b * b);
      float v1 = F_(r0.w) + F_(r1.w) + 128.f * (c * c + d * d);
      v0 += __shfl_xor_sync(~0u, v0, 1); v1 += __shfl_xor_sync(~0u, v1, 1);
      v0 += __shfl_xor_sync(~0u, v0, 2); v1 += __shfl_xor_sync(~0u, v1, 2);
      const float rs0 = rsqrtf(v0 * (1.f / 1024) + 1e-5f), rs1 = rsqrtf(v1 * (1.f / 1024) + 1e-5f);
      const float k0 = (s0 - m0) * rs0, k1 = (s1 - m1) * rs1;
      uint4 pc[4], ph_[4];
#pragma unroll
      for (int j = 0; j < 8; j++) {
        if (j == 0) {
#pragma unroll
          for (int i = 0; i < 4; i++) { pc[i] = lds4(prm + 256 + i * 64); ph_[i] = lds4(prm + 512 + i * 64); }
        }
        const uint32_t c0 = (j & 1) ? pc[j >> 1].z : pc[j >> 1].x, c1 = (j & 1) ? pc[j >> 1].w : pc[j >> 1].y;
        const uint32_t h0 = (j & 1) ? ph_[j >> 1].z : ph_[j >> 1].x, h1 = (j & 1) ? ph_[j >> 1].w : ph_[j >> 1].y;
        const float* d = acc + j * 8;
        stsm4((stw ^ ((j & 3) * 32)) + (j >> 2) * 16384,
              pk(fmaf(d[0], rs0, fmaf(k0, blo(c0), blo(h0))), fmaf(d[1], rs0, fmaf(k0, bhi(c0), bhi(h0)))),
              pk(fmaf(d[2], rs1, fmaf(k1, blo(c0), blo(h0))), fmaf(d[3], rs1, fmaf(k1, bhi(c0), bhi(h0)))),
              pk(fmaf(d[4], rs0, fmaf(k0, blo(c1), blo(h1))), fmaf(d[5], rs0, fmaf(k0, bhi(c1), bhi(h1)))),
              pk(fmaf(d[6], rs1, fmaf(k1, blo(c1), blo(h1))), fmaf(d[7], rs1, fmaf(k1, bhi(c1), bhi(h1)))));
      }
      FENCE_ASYNC_SMEM();
      __syncwarp();
      asm volatile("{.reg .pred p; elect.sync _|p, 0xffffffff; @p cp.async.bulk.global.shared::cta.bulk_group [%0],[%1],2048;\n"
                   "@p cp.async.bulk.global.shared::cta.bulk_group [%0+16384],[%1+16384],2048; cp.async.bulk.commit_group;}"
                   ::"l"(g_h2 + (size_t)(rb * 16 + nb * 2) * 1024 + row0 * 8), "r"(stg) : "memory");
      if (wg) BAR_SYNC(2, 128); else BAR_SYNC(3, 128);
    }
    PH(8); if (tid == 0) FT(14);
    const uint4* dst = UBASE + nb * 7 * 1024 + row0 * 8;
    int st = (64 - GT) % 6, prev = 0, flip = 0; uint32_t ph = (64 - GT) / 6 & 1, bs = sb + PRM + 1280 + q * 32;
#define NEXT() do { prev = st; if (++st == 6) { st = 0; ph ^= 1; } } while (0)
#define QUAD(N, acc, u, t, off, first) \
_Pragma("unroll") \
      for (int i = 0; i < 4; i++) { \
        const uint2 b = lds2u(bs + i * 8); \
        ffn_issue<N>(acc, full + st * 8, ph, aw + (off), bw + (off), i == 0 && (first)); \
        if (i == 0 && (t)) { ffn_store(stg + flip, dst); flip ^= 16384; dst += 1024; } \
        if (i == 3 && ((t) == 2 || (t) == 4)) ffn_done(cnt + (t) * 16); \
        WG_WAIT(1); \
        ffn_release(leader, emp + prev * 8); \
        NEXT(); \
        ffn_gelu(u, i, b, stw + flip, mp.zero[0]); \
      } \
      bs += 128;
    uint32_t u0[64], u1[48];
    {
      float acc[128];
#pragma unroll 1
      for (int k = 0; k < 16; k++) {
        ffn_issue<256>(acc, full + st * 8, ph, aw + (k < 2 ? STG / 16 + k * 1024 : (k & 3) * 3072), bw + (k & 3) * 3072, k == 0);
        if (tid == 0 && (k & 7) == 0) FT(15 + (k >> 3));
        if (k == 0) { ffn_done(cnt); if (tid == 0) FT(32); }
        if (FTS_ != 2 && tid == 0 && k && k < 5) FT(59 + k);
        WG_WAIT(1);
        ffn_release(leader && k, emp + prev * 8);
        NEXT();
      }
      WG_WAIT(0);
      acc_fence<128>(acc);
#pragma unroll
      for (int i = 0; i < 64; i++) u0[i] = pk(acc[2 * i], acc[2 * i + 1]);
    }
    PH(9); if (tid == 0) FT(17);
    {
      float acc[96];
#pragma unroll 1
      for (int t = 0; t < 4; t++) {
        if (FTS_ != 2 && tid == 0) FT(42 + t);
        QUAD(192, acc, u0, t, i * 3072, t == 0)
      }
      WG_WAIT(0);
      acc_fence<96>(acc);
#pragma unroll
      for (int i = 0; i < 48; i++) u1[i] = pk(acc[2 * i], acc[2 * i + 1]);
    }
    {
      float acc[64];
#pragma unroll 1
      for (int t = 4; t < 7; t++) {
        if (FTS_ != 2 && tid == 0) FT(42 + t);
        QUAD(128, acc, u1, t, SL(st) * 2048, t == 4)
      }
      uint4 pg[4], pb[4];
#pragma unroll
      for (int i = 0; i < 4; i++) { pg[i] = lds4(prm + 768 + i * 64); pb[i] = lds4(prm + 1024 + i * 64); }
#pragma unroll 1
      for (int k = 12; k < 56; k++) {
        if (FTS_ != 2 && tid == 0 && (k & 3) == 0) FT(46 + (k >> 2));
        ffn_issue<128>(acc, full + st * 8, ph, aw + SL(st) * 2048, bw + SL(st) * 2048, false);
        if (k == 12) ffn_store(stg + flip, dst);
        if (k == 16) ffn_done(cnt + 96);
        WG_WAIT(1);
        ffn_release(leader, emp + prev * 8);
        NEXT();
      }
      WG_WAIT(0);
      acc_fence<64>(acc);
      PH(13); if (tid == 0) { FT(30); FC(39); }
#pragma unroll
      for (int j = 0; j < 8; j++) {
        const uint32_t g0 = (j & 1) ? pg[j >> 1].z : pg[j >> 1].x, g1 = (j & 1) ? pg[j >> 1].w : pg[j >> 1].y;
        const uint32_t h0 = (j & 1) ? pb[j >> 1].z : pb[j >> 1].x, h1 = (j & 1) ? pb[j >> 1].w : pb[j >> 1].y;
        const float* d = acc + j * 8;
        const uint32_t* xv = x1 + j * 4;
        stsm4((stw ^ ((j & 3) * 32)) + (j >> 2) * 16384,
              pk(blo(xv[0]) + blo(g0) * (d[0] + blo(h0)), bhi(xv[0]) + bhi(g0) * (d[1] + bhi(h0))),
              pk(blo(xv[1]) + blo(g0) * (d[2] + blo(h0)), bhi(xv[1]) + bhi(g0) * (d[3] + bhi(h0))),
              pk(blo(xv[2]) + blo(g1) * (d[4] + blo(h1)), bhi(xv[2]) + bhi(g1) * (d[5] + bhi(h1))),
              pk(blo(xv[3]) + blo(g1) * (d[6] + blo(h1)), bhi(xv[3]) + bhi(g1) * (d[7] + bhi(h1))));
        if ((j & 3) == 3) {
          FENCE_ASYNC_SMEM();
          __syncwarp();
          asm volatile("{.reg .pred p; elect.sync _|p, 0xffffffff; @p cp.async.bulk.tensor.2d.global.shared::cta.bulk_group [%0,{%1,%2}],[%3];}"
                       ::"l"(&mp.out), "r"(nb * 128 + (j >> 2) * 64), "r"(rb * 128 + row0), "r"(stg + (j >> 2) * 16384) : "memory");
          if (j == 3) { SCHED_FENCE(47); acc_fence<32>(acc + 32); }
        }
      }
      BULK_COMMIT(); BULK_WAIT_READ(0);
    }
    PH(14); if (tid == 0) FT(31);
  }
}

typedef CUresult (*EncFn)(CUtensorMap*, CUtensorMapDataType, cuuint32_t, void*, const cuuint64_t*, const cuuint64_t*, const cuuint32_t*,
                          const cuuint32_t*, CUtensorMapInterleave, CUtensorMapSwizzle, CUtensorMapL2promotion, CUtensorMapFloatOOBfill);
static void map2d(EncFn enc, CUtensorMap* m, const void* p, int rows, int cols, int boxRows) {
  cuuint64_t d[2] = {(cuuint64_t)cols, (cuuint64_t)rows}, s[1] = {(cuuint64_t)cols * 2};
  cuuint32_t b[2] = {64, (cuuint32_t)boxRows}, e[2] = {1, 1};
  enc(m, CU_TENSOR_MAP_DATA_TYPE_BFLOAT16, 2, (void*)p, d, s, b, e, CU_TENSOR_MAP_INTERLEAVE_NONE, CU_TENSOR_MAP_SWIZZLE_128B,
      CU_TENSOR_MAP_L2_PROMOTION_L2_128B, CU_TENSOR_MAP_FLOAT_OOB_FILL_NONE);
}
static void map3d(EncFn enc, CUtensorMap* m, const void* p, int rows, int cols, int nch) {
  cuuint64_t d[3] = {64, (cuuint64_t)rows, (cuuint64_t)(cols / 64)}, s[2] = {(cuuint64_t)cols * 2, 128};
  cuuint32_t b[3] = {64, 64, (cuuint32_t)nch}, e[3] = {1, 1, 1};
  enc(m, CU_TENSOR_MAP_DATA_TYPE_BFLOAT16, 3, (void*)p, d, s, b, e, CU_TENSOR_MAP_INTERLEAVE_NONE, CU_TENSOR_MAP_SWIZZLE_128B,
      CU_TENSOR_MAP_L2_PROMOTION_L2_128B, CU_TENSOR_MAP_FLOAT_OOB_FILL_NONE);
}

extern "C" void kernel_launch(void* const* d_in, const int* in_sizes, int n_in, void* d_out, int out_size) {
  const bf16* x = (const bf16*)d_in[0];
  const bf16* mem0 = (const bf16*)d_in[1];
  void* fn = nullptr;
  cudaDriverEntryPointQueryResult qr;
  cudaGetDriverEntryPoint("cuTensorMapEncodeTiled", &fn, cudaEnableDefault, &qr);
  EncFn enc = (EncFn)fn;
  FfnMaps fm = {};
  map3d(enc, &fm.wo, d_in[5], 4096, 1024, 2);
  map3d(enc, &fm.w1a, d_in[8], 1024, 3584, 4);
  map3d(enc, &fm.w1b, d_in[8], 1024, 3584, 3);
  map3d(enc, &fm.w2, d_in[10], 3584, 1024, 2);
  map2d(enc, &fm.x, x, 2048, 1024, 128);
  map2d(enc, &fm.out, d_out, 2048, 1024, 16);
  map3d(enc, &fm.wo4, d_in[5], 4096, 1024, 4);
  {
    void* xp = nullptr;
    cudaGetSymbolAddress(&xp, g_xp);
    map2d(enc, &fm.xp, xp, 2048, 1024, 128);
    map2d(enc, &fm.xps, xp, 2048, 1024, 16);
  }
  RecMaps rm = {};
  map2d(enc, &rm.wq, d_in[2], 1024, 4096, 128);
  map2d(enc, &rm.wk, d_in[3], 1024, 4096, 128);
  map2d(enc, &rm.wv, d_in[4], 1024, 4096, 16);
  map2d(enc, &rm.wo, d_in[5], 4096, 1024, 128);
  map3d(enc, &rm.wm3, d_in[13], 1024, 6144, 8);
  {
    cuuint64_t d[2] = {6144, 1024}, sd[1] = {12288};
    cuuint32_t bi[2] = {256, 32}, e[2] = {1, 1};
    enc(&rm.wm, CU_TENSOR_MAP_DATA_TYPE_BFLOAT16, 2, d_in[13], d, sd, bi, e, CU_TENSOR_MAP_INTERLEAVE_NONE, CU_TENSOR_MAP_SWIZZLE_NONE,
        CU_TENSOR_MAP_L2_PROMOTION_NONE, CU_TENSOR_MAP_FLOAT_OOB_FILL_NONE);
  }
  {
    void* hp = nullptr;
    cudaGetSymbolAddress(&hp, g_h);
    cuuint64_t d[3] = {64, 32, 1024}, sd[2] = {128, 4096};
    cuuint32_t bi[3] = {64, 16, 16}, e[3] = {1, 1, 1};
    enc(&rm.hst, CU_TENSOR_MAP_DATA_TYPE_BFLOAT16, 3, hp, d, sd, bi, e, CU_TENSOR_MAP_INTERLEAVE_NONE, CU_TENSOR_MAP_SWIZZLE_NONE,
        CU_TENSOR_MAP_L2_PROMOTION_NONE, CU_TENSOR_MAP_FLOAT_OOB_FILL_NONE);
  }
  {
    void* ar = nullptr;
    cudaGetSymbolAddress(&ar, g_ar);
    cuuint64_t d[2] = {512, 160}, sd[1] = {1024};
    cuuint32_t bi[2] = {64, 40}, e[2] = {1, 1};
    enc(&rm.ari, CU_TENSOR_MAP_DATA_TYPE_BFLOAT16, 2, ar, d, sd, bi, e, CU_TENSOR_MAP_INTERLEAVE_NONE, CU_TENSOR_MAP_SWIZZLE_NONE,
        CU_TENSOR_MAP_L2_PROMOTION_NONE, CU_TENSOR_MAP_FLOAT_OOB_FILL_NONE);
  }
  cudaFuncSetAttribute(k_ffn, cudaFuncAttributeMaxDynamicSharedMemorySize, ffn::SMEM);
  cudaFuncSetAttribute(k_rec, cudaFuncAttributeMaxDynamicSharedMemorySize, rec::SMEM);
  char* xc = nullptr;
  cudaGetSymbolAddress((void**)&xc, g_xc);
  xc += (0 - (uintptr_t)xc) & 0x3FFFF;
  {
    cuuint64_t d[5] = {256, 4, 2, 2, 1024}, sd[4] = {rec::XC, 512, 2048, 8192};
    cuuint32_t bi[5] = {256, 4, 2, 1, 1}, e[5] = {1, 1, 1, 1, 1};
    enc(&rm.vx, CU_TENSOR_MAP_DATA_TYPE_BFLOAT16, 5, xc, d, sd, bi, e, CU_TENSOR_MAP_INTERLEAVE_NONE, CU_TENSOR_MAP_SWIZZLE_NONE,
        CU_TENSOR_MAP_L2_PROMOTION_NONE, CU_TENSOR_MAP_FLOAT_OOB_FILL_NONE);
  }
  cudaStream_t st = cudaStreamPerThread;
  int dF = 450, dA = 2700, dS = 300, dM = 120, dG = 350, dP = 24, dX = 48, dD = 350, dZ = 0, dZ2 = 1, dV = 370, dX2 = 60;
  k_rec<<<132, 512, rec::SMEM, st>>>(rm, mem0, x, (const bf16*)d_in[12], (const bf16*)d_in[13], (const bf16*)d_in[5], xc, dF, dA, dS, dM, dG, dP, dX, dD, dZ, dZ2, dV, dX2);
  cudaLaunchConfig_t cfg = {};
  cfg.gridDim = dim3(132); cfg.blockDim = dim3(384); cfg.dynamicSmemBytes = ffn::SMEM; cfg.stream = st;
  cudaLaunchAttribute at[1];
  at[0].id = cudaLaunchAttributeProgrammaticStreamSerialization;
  at[0].val.programmaticStreamSerializationAllowed = 1;
  cfg.attrs = at; cfg.numAttrs = 1;
  cudaLaunchKernelEx(&cfg, k_ffn, fm, (const bf16*)d_in[9], (const bf16*)d_in[11], (const char*)x);
}
```

```cpp
#include <cuda_runtime.h>
#include <cuda.h>
#include <cuda_bf16.h>
#include <stdint.h>

typedef __nv_bfloat16 bf16;

__device__ __align__(16) float g_mod[6144];
__device__ __align__(1024) uint4 g_modp[4 * 512];
__device__ __align__(128) uint4 g_hsm[8];
__device__ __align__(128) unsigned g_fcnt_[32];
__device__ __align__(128) uint4 g_hprog_[8];
#define g_fcnt g_fcnt_[0]
#define g_hprog g_hprog_[0]
__device__ __align__(1024) uint4 g_h[2048 * 1024 / 8];
__device__ __align__(1024) uint4 g_O[2048 * 4096 / 8];
__device__ __align__(1024) uint4 g_h2[2048 * 1024 / 8];
__device__ __align__(1024) uint4 g_xp[2048 * 1024 / 8];
__device__ __align__(1024) unsigned g_oc[2 * 16 * 32];
__device__ __align__(1024) uint4 g_stat[2048 * 4];
__device__ __align__(1024) unsigned g_cnt[16 * 4 * 32];
__device__ __align__(1024) uint4 g_ar[160 * 64];
__device__ __align__(1024) uint4 g_xc[33 * 16384];
__device__ __align__(1024) unsigned g_tm[128 * 8];
#define PH(i)
#define FT(i)
#define PT(i)
#define PTT(i, t)
#define PDUMP()
#define PZERO()
#define FC(i)
#define RP(i)
#define RPN(i, s)
#define TSV(i, v)
#define TS(i)

#define FTS_ 0
#define NB1 2
#define NB2 3
#define IB2 14
#define IB3 11
#define IV 3
#define LD1 1000
#define LD2 800
#define LD3 8000
#define VDL 100
#define GT 12
#define HPS 400
#define HPR 512
#define HPW 2
#define PDS 2
#define VW 1
#define NH 4
#define NWA 2
#define NWB 7
#define VO 5
#define VE 1
#define WPC 3
#define WPA 4
#define LG 1
#define NCS 1
#define NWQ 10
#define AT8 1
#define X1 1
#define XD1 400
#define TMP 1
#define HREL "relaxed"
constexpr int WIN = 2, RF_ = 208, RA_ = 488 - 2 * RF_;
#define SPIN_LIMIT (1 << 20)
__device__ __forceinline__ uint64_t mkdesc(uint32_t addr, uint32_t lbo, uint32_t sbo) {
  return (uint64_t)((addr & 0x3FFFF) >> 4) | ((uint64_t)(lbo >> 4) << 16) | ((uint64_t)(sbo >> 4) << 32) | (1ull << 62);
}
__device__ __forceinline__ void mbar_init(uint32_t a, int c) { asm volatile("mbarrier.init.shared.b64 [%0],%1;" ::"r"(a), "r"(c) : "memory"); }
__device__ __forceinline__ void mbar_wait(uint32_t a, uint32_t par) {
  asm volatile(
      "{.reg .pred p; .reg .u32 n;\n"
      "mov.u32 n, 0;\n"
      "W: mbarrier.try_wait.parity.shared.b64 p,[%0],%1;\n"
      "@p bra D;\n"
      "add.u32 n, n, 1;\n"
      "setp.lt.u32 p, n, %2;\n"
      "@p bra W;\n"
      "trap;\n"
      "D:}" ::"r"(a), "r"(par), "n"(SPIN_LIMIT) : "memory");
}
__device__ __forceinline__ void mbar_wait_q(uint32_t a, uint32_t par) {
  asm volatile(
      "{.reg .pred p; .reg .u32 n;\n"
      "mov.u32 n, 0;\n"
      "W: mbarrier.try_wait.parity.shared.b64 p,[%0],%1,4000;\n"
      "@p bra D;\n"
      "add.u32 n, n, 1;\n"
      "setp.lt.u32 p, n, %2;\n"
      "@p bra W;\n"
      "trap;\n"
      "D:}" ::"r"(a), "r"(par), "n"(SPIN_LIMIT / 16) : "memory");
}
__device__ __forceinline__ void mbar_expect(uint32_t a, uint32_t b) { asm volatile("mbarrier.arrive.expect_tx.shared.b64 _,[%0],%1;" ::"r"(a), "r"(b) : "memory"); }
__device__ __forceinline__ uint32_t mapa(uint32_t a, uint32_t cta) { uint32_t r; asm("mapa.shared::cluster.u32 %0,%1,%2;" : "=r"(r) : "r"(a), "r"(cta)); return r; }
__device__ __forceinline__ void mbar_arrive_cl(uint32_t a) { asm volatile("mbarrier.arrive.shared::cluster.b64 _,[%0];" ::"r"(a) : "memory"); }
__device__ __forceinline__ void tma2d(uint32_t dst, const CUtensorMap* m, int c0, int c1, uint32_t mb) {
  asm volatile("cp.async.bulk.tensor.2d.shared::cluster.global.mbarrier::complete_tx::bytes [%0],[%1,{%2,%3}],[%4];" ::"r"(dst), "l"(m), "r"(c0), "r"(c1), "r"(mb) : "memory");
}
__device__ __forceinline__ uint64_t pol_stream() { uint64_t p; asm("createpolicy.fractional.L2::evict_first.b64 %0, 1.0;" : "=l"(p)); return p; }
__device__ __forceinline__ void tma2d_s(uint32_t dst, const CUtensorMap* m, int c0, int c1, uint32_t mb) {
  asm volatile("cp.async.bulk.tensor.2d.shared::cluster.global.mbarrier::complete_tx::bytes.L2::cache_hint [%0],[%1,{%2,%3}],[%4],%5;" ::"r"(dst), "l"(m), "r"(c0), "r"(c1), "r"(mb), "l"(pol_stream()) : "memory");
}
__device__ __forceinline__ void tma2d_pf(const CUtensorMap* m, int c0, int c1) {
  asm volatile("cp.async.bulk.prefetch.tensor.2d.L2.global [%0,{%1,%2}];" ::"l"(m), "r"(c0), "r"(c1) : "memory");
}
template <bool STREAM = false>
__device__ __forceinline__ void e_expect_tma3d(uint32_t dst, const CUtensorMap* m, int c1, int c2, uint32_t mb, uint32_t bytes) {
  if (STREAM) asm volatile("{.reg .pred p; elect.sync _|p, 0xffffffff; @p mbarrier.arrive.expect_tx.shared.b64 _,[%4],%5;\n"
               "@p cp.async.bulk.tensor.3d.shared::cluster.global.mbarrier::complete_tx::bytes.L2::cache_hint [%0],[%1,{0,%2,%3}],[%4],%6;}" ::"r"(dst), "l"(m), "r"(c1), "r"(c2), "r"(mb), "r"(bytes), "l"(pol_stream()) : "memory");
  else asm volatile("{.reg .pred p; elect.sync _|p, 0xffffffff; @p mbarrier.arrive.expect_tx.shared.b64 _,[%4],%5;\n"
               "@p cp.async.bulk.tensor.3d.shared::cluster.global.mbarrier::complete_tx::bytes [%0],[%1,{0,%2,%3}],[%4];}" ::"r"(dst), "l"(m), "r"(c1), "r"(c2), "r"(mb), "r"(bytes) : "memory");
}
template <bool STREAM = false>
__device__ __forceinline__ void e_bulk_ld(uint32_t dst, const void* src, uint32_t n, uint32_t mb) {
  if (STREAM) asm volatile("{.reg .pred p; elect.sync _|p, 0xffffffff; @p cp.async.bulk.shared::cluster.global.mbarrier::complete_tx::bytes.L2::cache_hint [%0],[%1],%2,[%3],%4;}" ::"r"(dst), "l"(src), "r"(n), "r"(mb), "l"(pol_stream()) : "memory");
  else asm volatile("{.reg .pred p; elect.sync _|p, 0xffffffff; @p cp.async.bulk.shared::cluster.global.mbarrier::complete_tx::bytes [%0],[%1],%2,[%3];}" ::"r"(dst), "l"(src), "r"(n), "r"(mb) : "memory");
}
#define BULK_COMMIT() asm volatile("cp.async.bulk.commit_group;" ::: "memory")
#define BULK_WAIT_READ(n) asm volatile("cp.async.bulk.wait_group.read " #n ";" ::: "memory")
#define FENCE_ASYNC_SMEM() asm volatile("fence.proxy.async.shared::cta;" ::: "memory")
#define FENCE_ASYNC_G() asm volatile("fence.proxy.async.global;" ::: "memory")
#define WG_FENCE() asm volatile("wgmma.fence.sync.aligned;" ::: "memory")
#define WG_COMMIT() asm volatile("wgmma.commit_group.sync.aligned;" ::: "memory")
#define WG_WAIT(n) asm volatile("wgmma.wait_group.sync.aligned " #n ";" ::: "memory")
#define BAR_SYNC(id, n) asm volatile("bar.sync %0,%1;" ::"n"(id), "n"(n) : "memory")
#define BAR_ARRIVE(id, n) asm volatile("bar.arrive %0,%1;" ::"n"(id), "n"(n) : "memory")
#define SCHED_FENCE(k) asm volatile("{.reg .pred p; setp.ne.u32 p,%0,0; @p trap;}" ::"r"(mp.zero[(k) - 46]) : "memory")
#define CLUSTER_ARRIVE() asm volatile("fence.release.sync_restrict::shared::cta.cluster; barrier.cluster.arrive.relaxed.aligned;" ::: "memory")
#define CLUSTER_WAIT() asm volatile("barrier.cluster.wait.aligned;" ::: "memory")
#define CLUSTER_SYNC() do { CLUSTER_ARRIVE(); CLUSTER_WAIT(); } while (0)
__device__ __forceinline__ uint32_t pk(float lo, float hi) { uint32_t r; asm("cvt.rn.bf16x2.f32 %0,%1,%2;" : "=r"(r) : "f"(hi), "f"(lo)); return r; }
__device__ __forceinline__ float blo(uint32_t v) { return __uint_as_float(v << 16); }
__device__ __forceinline__ float bhi(uint32_t v) { return __uint_as_float(v & 0xffff0000u); }
__device__ __forceinline__ void ldsm4(uint32_t* r, uint32_t a) {
  asm volatile("ldmatrix.sync.aligned.m8n8.x4.shared.b16 {%0,%1,%2,%3},[%4];" : "=r"(r[0]), "=r"(r[1]), "=r"(r[2]), "=r"(r[3]) : "r"(a) : "memory");
}
__device__ __forceinline__ void ldsm4t(uint32_t* r, uint32_t a) {
  asm volatile("ldmatrix.sync.aligned.m8n8.x4.trans.shared.b16 {%0,%1,%2,%3},[%4];" : "=r"(r[0]), "=r"(r[1]), "=r"(r[2]), "=r"(r[3]) : "r"(a) : "memory");
}
__device__ __forceinline__ void stsm4(uint32_t a, uint32_t r0, uint32_t r1, uint32_t r2, uint32_t r3) {
  asm volatile("stmatrix.sync.aligned.m8n8.x4.shared.b16 [%0],{%1,%2,%3,%4};" ::"r"(a), "r"(r0), "r"(r1), "r"(r2), "r"(r3) : "memory");
}
__device__ __forceinline__ void mma16(float* d, uint32_t a0, uint32_t a1, uint32_t a2, uint32_t a3, uint32_t b0, uint32_t b1) {
  asm volatile("mma.sync.aligned.m16n8k16.row.col.f32.bf16.bf16.f32 {%0,%1,%2,%3},{%4,%5,%6,%7},{%8,%9},{%0,%1,%2,%3};"
               : "+f"(d[0]), "+f"(d[1]), "+f"(d[2]), "+f"(d[3]) : "r"(a0), "r"(a1), "r"(a2), "r"(a3), "r"(b0), "r"(b1));
}
__device__ __forceinline__ void mma8(float* d, uint32_t a0, uint32_t a1, uint32_t b0) {
  asm volatile("mma.sync.aligned.m16n8k8.row.col.f32.bf16.bf16.f32 {%0,%1,%2,%3},{%4,%5},{%6},{%0,%1,%2,%3};"
               : "+f"(d[0]), "+f"(d[1]), "+f"(d[2]), "+f"(d[3]) : "r"(a0), "r"(a1), "r"(b0));
}
__device__ __forceinline__ float4 lds4f(uint32_t a) { float4 v; asm volatile("ld.shared.v4.f32 {%0,%1,%2,%3},[%4];" : "=f"(v.x), "=f"(v.y), "=f"(v.z), "=f"(v.w) : "r"(a) : "memory"); return v; }
__device__ __forceinline__ uint4 lds4(uint32_t a) { uint4 v; asm volatile("ld.shared.v4.u32 {%0,%1,%2,%3},[%4];" : "=r"(v.x), "=r"(v.y), "=r"(v.z), "=r"(v.w) : "r"(a) : "memory"); return v; }
__device__ __forceinline__ uint2 lds2u(uint32_t a) { uint2 v; asm volatile("ld.shared.v2.u32 {%0,%1},[%2];" : "=r"(v.x), "=r"(v.y) : "r"(a) : "memory"); return v; }
__device__ __forceinline__ uint32_t lds1(uint32_t a) { uint32_t v; asm volatile("ld.shared.u32 %0,[%1];" : "=r"(v) : "r"(a) : "memory"); return v; }
__device__ __forceinline__ void sts4(uint32_t a, uint32_t x, uint32_t y, uint32_t z, uint32_t w) { asm volatile("st.shared.v4.u32 [%0],{%1,%2,%3,%4};" ::"r"(a), "r"(x), "r"(y), "r"(z), "r"(w) : "memory"); }
__device__ __forceinline__ void sts1(uint32_t a, uint32_t x) { asm volatile("st.shared.u32 [%0],%1;" ::"r"(a), "r"(x) : "memory"); }
__device__ __forceinline__ void sta4(uint32_t a, const uint32_t* v, uint32_t mb) {
  asm volatile("st.async.shared::cluster.mbarrier::complete_tx::bytes.v4.b32 [%0],{%1,%2,%3,%4},[%5];" ::"r"(a), "r"(v[0]), "r"(v[1]), "r"(v[2]), "r"(v[3]), "r"(mb) : "memory");
}
__device__ __forceinline__ uint4 ldg_rlx4(const void* p) { uint4 v; asm volatile("ld.relaxed.gpu.global.v4.u32 {%0,%1,%2,%3},[%4];" : "=r"(v.x), "=r"(v.y), "=r"(v.z), "=r"(v.w) : "l"(p) : "memory"); return v; }
__device__ __forceinline__ uint4 ldg_b128(const void* p) {
  uint4 v;
  asm volatile("{.reg .b128 t; .reg .b64 a,b; ld.relaxed.gpu.global.b128 t,[%4]; mov.b128 {a,b},t; mov.b64 {%0,%1},a; mov.b64 {%2,%3},b;}" : "=r"(v.x), "=r"(v.y), "=r"(v.z), "=r"(v.w) : "l"(p) : "memory");
  return v;
}
__device__ __forceinline__ void stg_b128(void* p, uint32_t x, uint32_t y, uint32_t z, uint32_t w) {
  asm volatile("{.reg .b128 t; .reg .b64 a,b; mov.b64 a,{%1,%2}; mov.b64 b,{%3,%4}; mov.b128 t,{a,b}; st.relaxed.gpu.global.b128 [%0],t;}" ::"l"(p), "r"(x), "r"(y), "r"(z), "r"(w) : "memory");
}
__device__ __forceinline__ unsigned ld_acq(const unsigned* p) { unsigned v; asm volatile("ld.acquire.gpu.global.u32 %0,[%1];" : "=r"(v) : "l"(p) : "memory"); return v; }
__device__ __forceinline__ void wait_cnt(const unsigned* p, unsigned n) { int it = 0; while (ld_acq(p) < n) { if (++it > SPIN_LIMIT) __trap(); } }
__device__ __forceinline__ void wait_h(unsigned n) {
  int it = 0;
  while (true) {
    uint4 v;
    asm volatile("{.reg .b128 t; .reg .b64 a,b; ld.acquire.gpu.global.b128 t,[%4]; mov.b128 {a,b},t; mov.b64 {%0,%1},a; mov.b64 {%2,%3},b;}" : "=r"(v.x), "=r"(v.y), "=r"(v.z), "=r"(v.w) : "l"(&g_hprog) : "memory");
    if (min(min(v.x, v.y), min(v.z, v.w)) > n) break;
    if (++it > SPIN_LIMIT) __trap();
    __nanosleep(200);
  }
  FENCE_ASYNC_G();
}
__device__ __forceinline__ uint32_t clk() { uint32_t c; asm volatile("mov.u32 %0,%%clock;" : "=r"(c)); return c; }
__device__ __forceinline__ uint32_t gtime() { uint32_t c; asm volatile("mov.u32 %0,%%globaltimer_lo;" : "=r"(c)); return c; }
__device__ __forceinline__ void wait_until(uint32_t t0, uint32_t d) { while (clk() - t0 < d) {} }
__device__ __forceinline__ float ex2(float x) { float r; asm("ex2.approx.ftz.f32 %0,%1;" : "=f"(r) : "f"(x)); return r; }
__device__ __forceinline__ float silu(float x) { return __fdividef(x, 1.f + __expf(-x)); }
__device__ __forceinline__ float rbf(float x) { return __bfloat162float(__float2bfloat16_rn(x)); }

__device__ __forceinline__ void wgmma_ss_n128(float* d, uint64_t a, uint64_t b, int sd) {
  asm volatile("{.reg .pred p; setp.ne.b32 p, %66, 0;\n"
    "wgmma.mma_async.sync.aligned.m64n128k16.f32.bf16.bf16 {%0,%1,%2,%3,%4,%5,%6,%7,%8,%9,%10,%11,%12,%13,%14,%15,%16,%17,%18,%19,%20,%21,%22,%23,%24,%25,%26,%27,%28,%29,%30,%31,%32,%33,%34,%35,%36,%37,%38,%39,%40,%41,%42,%43,%44,%45,%46,%47,%48,%49,%50,%51,%52,%53,%54,%55,%56,%57,%58,%59,%60,%61,%62,%63}, %64, %65, p, 1, 1, 0, 1;}\n"
    : "+f"(d[0]),"+f"(d[1]),"+f"(d[2]),"+f"(d[3]),"+f"(d[4]),"+f"(d[5]),"+f"(d[6]),"+f"(d[7]),
      "+f"(d[8]),"+f"(d[9]),"+f"(d[10]),"+f"(d[11]),"+f"(d[12]),"+f"(d[13]),"+f"(d[14]),"+f"(d[15]),
      "+f"(d[16]),"+f"(d[17]),"+f"(d[18]),"+f"(d[19]),"+f"(d[20]),"+f"(d[21]),"+f"(d[22]),"+f"(d[23]),
      "+f"(d[24]),"+f"(d[25]),"+f"(d[26]),"+f"(d[27]),"+f"(d[28]),"+f"(d[29]),"+f"(d[30]),"+f"(d[31]),
      "+f"(d[32]),"+f"(d[33]),"+f"(d[34]),"+f"(d[35]),"+f"(d[36]),"+f"(d[37]),"+f"(d[38]),"+f"(d[39]),
      "+f"(d[40]),"+f"(d[41]),"+f"(d[42]),"+f"(d[43]),"+f"(d[44]),"+f"(d[45]),"+f"(d[46]),"+f"(d[47]),
      "+f"(d[48]),"+f"(d[49]),"+f"(d[50]),"+f"(d[51]),"+f"(d[52]),"+f"(d[53]),"+f"(d[54]),"+f"(d[55]),
      "+f"(d[56]),"+f"(d[57]),"+f"(d[58]),"+f"(d[59]),"+f"(d[60]),"+f"(d[61]),"+f"(d[62]),"+f"(d[63])
    : "l"(a), "l"(b), "r"(sd));
}
__device__ __forceinline__ void wgmma_ss_n192(float* d, uint64_t a, uint64_t b, int sd) {
  asm volatile("{.reg .pred p; setp.ne.b32 p, %98, 0;\n"
    "wgmma.mma_async.sync.aligned.m64n192k16.f32.bf16.bf16 {%0,%1,%2,%3,%4,%5,%6,%7,%8,%9,%10,%11,%12,%13,%14,%15,%16,%17,%18,%19,%20,%21,%22,%23,%24,%25,%26,%27,%28,%29,%30,%31,%32,%33,%34,%35,%36,%37,%38,%39,%40,%41,%42,%43,%44,%45,%46,%47,%48,%49,%50,%51,%52,%53,%54,%55,%56,%57,%58,%59,%60,%61,%62,%63,%64,%65,%66,%67,%68,%69,%70,%71,%72,%73,%74,%75,%76,%77,%78,%79,%80,%81,%82,%83,%84,%85,%86,%87,%88,%89,%90,%91,%92,%93,%94,%95}, %96, %97, p, 1, 1, 0, 1;}\n"
    : "+f"(d[0]),"+f"(d[1]),"+f"(d[2]),"+f"(d[3]),"+f"(d[4]),"+f"(d[5]),"+f"(d[6]),"+f"(d[7]),
      "+f"(d[8]),"+f"(d[9]),"+f"(d[10]),"+f"(d[11]),"+f"(d[12]),"+f"(d[13]),"+f"(d[14]),"+f"(d[15]),
      "+f"(d[16]),"+f"(d[17]),"+f"(d[18]),"+f"(d[19]),"+f"(d[20]),"+f"(d[21]),"+f"(d[22]),"+f"(d[23]),
      "+f"(d[24]),"+f"(d[25]),"+f"(d[26]),"+f"(d[27]),"+f"(d[28]),"+f"(d[29]),"+f"(d[30]),"+f"(d[31]),
      "+f"(d[32]),"+f"(d[33]),"+f"(d[34]),"+f"(d[35]),"+f"(d[36]),"+f"(d[37]),"+f"(d[38]),"+f"(d[39]),
      "+f"(d[40]),"+f"(d[41]),"+f"(d[42]),"+f"(d[43]),"+f"(d[44]),"+f"(d[45]),"+f"(d[46]),"+f"(d[47]),
      "+f"(d[48]),"+f"(d[49]),"+f"(d[50]),"+f"(d[51]),"+f"(d[52]),"+f"(d[53]),"+f"(d[54]),"+f"(d[55]),
      "+f"(d[56]),"+f"(d[57]),"+f"(d[58]),"+f"(d[59]),"+f"(d[60]),"+f"(d[61]),"+f"(d[62]),"+f"(d[63]),
      "+f"(d[64]),"+f"(d[65]),"+f"(d[66]),"+f"(d[67]),"+f"(d[68]),"+f"(d[69]),"+f"(d[70]),"+f"(d[71]),
      "+f"(d[72]),"+f"(d[73]),"+f"(d[74]),"+f"(d[75]),"+f"(d[76]),"+f"(d[77]),"+f"(d[78]),"+f"(d[79]),
      "+f"(d[80]),"+f"(d[81]),"+f"(d[82]),"+f"(d[83]),"+f"(d[84]),"+f"(d[85]),"+f"(d[86]),"+f"(d[87]),
      "+f"(d[88]),"+f"(d[89]),"+f"(d[90]),"+f"(d[91]),"+f"(d[92]),"+f"(d[93]),"+f"(d[94]),"+f"(d[95])
    : "l"(a), "l"(b), "r"(sd));
}
__device__ __forceinline__ void wgmma_ss_n256(float* d, uint64_t a, uint64_t b, int sd) {
  asm volatile("{.reg .pred p; setp.ne.b32 p, %130, 0;\n"
    "wgmma.mma_async.sync.aligned.m64n256k16.f32.bf16.bf16 {%0,%1,%2,%3,%4,%5,%6,%7,%8,%9,%10,%11,%12,%13,%14,%15,%16,%17,%18,%19,%20,%21,%22,%23,%24,%25,%26,%27,%28,%29,%30,%31,%32,%33,%34,%35,%36,%37,%38,%39,%40,%41,%42,%43,%44,%45,%46,%47,%48,%49,%50,%51,%52,%53,%54,%55,%56,%57,%58,%59,%60,%61,%62,%63,%64,%65,%66,%67,%68,%69,%70,%71,%72,%73,%74,%75,%76,%77,%78,%79,%80,%81,%82,%83,%84,%85,%86,%87,%88,%89,%90,%91,%92,%93,%94,%95,%96,%97,%98,%99,%100,%101,%102,%103,%104,%105,%106,%107,%108,%109,%110,%111,%112,%113,%114,%115,%116,%117,%118,%119,%120,%121,%122,%123,%124,%125,%126,%127}, %128, %129, p, 1, 1, 0, 1;}\n"
    : "+f"(d[0]),"+f"(d[1]),"+f"(d[2]),"+f"(d[3]),"+f"(d[4]),"+f"(d[5]),"+f"(d[6]),"+f"(d[7]),
      "+f"(d[8]),"+f"(d[9]),"+f"(d[10]),"+f"(d[11]),"+f"(d[12]),"+f"(d[13]),"+f"(d[14]),"+f"(d[15]),
      "+f"(d[16]),"+f"(d[17]),"+f"(d[18]),"+f"(d[19]),"+f"(d[20]),"+f"(d[21]),"+f"(d[22]),"+f"(d[23]),
      "+f"(d[24]),"+f"(d[25]),"+f"(d[26]),"+f"(d[27]),"+f"(d[28]),"+f"(d[29]),"+f"(d[30]),"+f"(d[31]),
      "+f"(d[32]),"+f"(d[33]),"+f"(d[34]),"+f"(d[35]),"+f"(d[36]),"+f"(d[37]),"+f"(d[38]),"+f"(d[39]),
      "+f"(d[40]),"+f"(d[41]),"+f"(d[42]),"+f"(d[43]),"+f"(d[44]),"+f"(d[45]),"+f"(d[46]),"+f"(d[47]),
      "+f"(d[48]),"+f"(d[49]),"+f"(d[50]),"+f"(d[51]),"+f"(d[52]),"+f"(d[53]),"+f"(d[54]),"+f"(d[55]),
      "+f"(d[56]),"+f"(d[57]),"+f"(d[58]),"+f"(d[59]),"+f"(d[60]),"+f"(d[61]),"+f"(d[62]),"+f"(d[63]),
      "+f"(d[64]),"+f"(d[65]),"+f"(d[66]),"+f"(d[67]),"+f"(d[68]),"+f"(d[69]),"+f"(d[70]),"+f"(d[71]),
      "+f"(d[72]),"+f"(d[73]),"+f"(d[74]),"+f"(d[75]),"+f"(d[76]),"+f"(d[77]),"+f"(d[78]),"+f"(d[79]),
      "+f"(d[80]),"+f"(d[81]),"+f"(d[82]),"+f"(d[83]),"+f"(d[84]),"+f"(d[85]),"+f"(d[86]),"+f"(d[87]),
      "+f"(d[88]),"+f"(d[89]),"+f"(d[90]),"+f"(d[91]),"+f"(d[92]),"+f"(d[93]),"+f"(d[94]),"+f"(d[95]),
      "+f"(d[96]),"+f"(d[97]),"+f"(d[98]),"+f"(d[99]),"+f"(d[100]),"+f"(d[101]),"+f"(d[102]),"+f"(d[103]),
      "+f"(d[104]),"+f"(d[105]),"+f"(d[106]),"+f"(d[107]),"+f"(d[108]),"+f"(d[109]),"+f"(d[110]),"+f"(d[111]),
      "+f"(d[112]),"+f"(d[113]),"+f"(d[114]),"+f"(d[115]),"+f"(d[116]),"+f"(d[117]),"+f"(d[118]),"+f"(d[119]),
      "+f"(d[120]),"+f"(d[121]),"+f"(d[122]),"+f"(d[123]),"+f"(d[124]),"+f"(d[125]),"+f"(d[126]),"+f"(d[127])
    : "l"(a), "l"(b), "r"(sd));
}
__device__ __forceinline__ void wgmma_rs_n32(float* d, const uint32_t* a, uint64_t b, int sd) {
  asm volatile("{.reg .pred p; setp.ne.b32 p, %21, 0;\n"
    "wgmma.mma_async.sync.aligned.m64n32k16.f32.bf16.bf16 {%0,%1,%2,%3,%4,%5,%6,%7,%8,%9,%10,%11,%12,%13,%14,%15}, {%16,%17,%18,%19}, %20, p, 1, 1, 0;}\n"
    : "+f"(d[0]),"+f"(d[1]),"+f"(d[2]),"+f"(d[3]),"+f"(d[4]),"+f"(d[5]),"+f"(d[6]),"+f"(d[7]),
      "+f"(d[8]),"+f"(d[9]),"+f"(d[10]),"+f"(d[11]),"+f"(d[12]),"+f"(d[13]),"+f"(d[14]),"+f"(d[15])
    : "r"(a[0]), "r"(a[1]), "r"(a[2]), "r"(a[3]), "l"(b), "r"(sd));
}
__device__ __forceinline__ void wgmma_ssT_n32(float* d, uint64_t a, uint64_t b, int sd) {
  asm volatile("{.reg .pred p; setp.ne.b32 p, %18, 0;\n"
    "wgmma.mma_async.sync.aligned.m64n32k16.f32.bf16.bf16 {%0,%1,%2,%3,%4,%5,%6,%7,%8,%9,%10,%11,%12,%13,%14,%15}, %16, %17, p, 1, 1, 1, 0;}\n"
    : "+f"(d[0]),"+f"(d[1]),"+f"(d[2]),"+f"(d[3]),"+f"(d[4]),"+f"(d[5]),"+f"(d[6]),"+f"(d[7]),
      "+f"(d[8]),"+f"(d[9]),"+f"(d[10]),"+f"(d[11]),"+f"(d[12]),"+f"(d[13]),"+f"(d[14]),"+f"(d[15])
    : "l"(a), "l"(b), "r"(sd));
}

__device__ __forceinline__ void wgmma_rs_n32_z(float* d, const uint32_t* a, uint64_t b) {
  asm volatile("{.reg .pred p; setp.ne.b32 p, 0, 0;\n"
    "wgmma.mma_async.sync.aligned.m64n32k16.f32.bf16.bf16 {%0,%1,%2,%3,%4,%5,%6,%7,%8,%9,%10,%11,%12,%13,%14,%15}, {%16,%17,%18,%19}, %20, p, 1, 1, 0;}\n"
    : "=f"(d[0]),"=f"(d[1]),"=f"(d[2]),"=f"(d[3]),"=f"(d[4]),"=f"(d[5]),"=f"(d[6]),"=f"(d[7]),
      "=f"(d[8]),"=f"(d[9]),"=f"(d[10]),"=f"(d[11]),"=f"(d[12]),"=f"(d[13]),"=f"(d[14]),"=f"(d[15])
    : "r"(a[0]), "r"(a[1]), "r"(a[2]), "r"(a[3]), "l"(b));
}

namespace rec {
constexpr int NVR = 5;
constexpr int NVS = 16 - NVR;
constexpr int NVP = 2;
constexpr int NWP = NWQ;
constexpr uint32_t WO = 0;
constexpr uint32_t XB = 65536;
constexpr uint32_t PK = XB + 32768;
constexpr uint32_t VN = PK + 24576;
constexpr uint32_t VX0 = VN + 4096;
constexpr uint32_t WVS = 131072;
constexpr uint32_t MEM = WVS + 2 * NVS * 2048;
constexpr uint32_t ARO = MEM + 10240;
constexpr uint32_t OB = ARO + 5120;
constexpr uint32_t QT = OB + 2048;
constexpr uint32_t KT = QT + 2048;
constexpr uint32_t RQ = KT + 6144;
constexpr uint32_t RK = RQ + 2048;
constexpr uint32_t SC = RK + 2048;
constexpr uint32_t OT = OB;
constexpr uint32_t SCT = 768, TFP = 9 * 128;
constexpr uint32_t TF = SC + 2 * SCT;
constexpr uint32_t PRE = MEM + 2 * NVR * 2048;
constexpr uint32_t TA = TF + 8 * TFP;
constexpr uint32_t RX = TA + 7168;
constexpr uint32_t VX1 = RX + 2048;
constexpr uint32_t BARS = VX1 + 4096;
constexpr uint32_t PACE = BARS + 18 * 8;
constexpr uint32_t SMEM = BARS + 512;
static_assert(PRE + 3072 <= TF, "staging");
constexpr int NW1 = NWA;
static_assert(SMEM <= 232448, "smem");
constexpr uint32_t T_MEM = 0, T_QK = 128, T_O = 256, T_WV = 384, T_WO = 512, T_AR = 640, T_PK = 768, T_VM = 896, T_RX = 1024;
constexpr int B_E = 2, B_SC = 3, B_S = 4, B_O = 5, B_F = 6, B_W = 7, B_C = 9, B_K = 10, B_H = 15, B_T0 = 0, B_Q = 1, B_S2 = 6, B_T2 = 9, B_P = 13, B_T = 14, B_R = 11, B_X = 12, B_V = 8;
constexpr int XC = 16384, X_RING = 131072, X_SC = 65536, X_TOK = 4096;
#define X_VX(i) (((i) >> 1) * 2048 + ((i) & 1) * 512)
#define X_VM(i) (X_VX(i) + 1024)
#define X_VRING(n) (((n) & 1) * X_RING + ((n) & 2) * 4096)
#define X_VTAG(n) ((((n) >> 2) + 1) & 1)
}
struct RecMaps { CUtensorMap wq, wk, wv, wo, ari, vx, wm, wm3, hst; int zero[40]; };

#define F_(x) __uint_as_float(x)
#define U_(x) __float_as_uint(x)
__device__ __forceinline__ void ar_fetch(uint32_t dst, const CUtensorMap* m, int slot, int half, uint32_t mb) {
  asm volatile("{.reg .pred p; elect.sync _|p, 0xffffffff; @p mbarrier.arrive.expect_tx.shared.b64 _,[%4],10240;\n"
               "@p cp.async.bulk.tensor.2d.shared::cluster.global.mbarrier::complete_tx::bytes [%0],[%1,{%2,%3}],[%4];\n"
               "@p cp.async.bulk.tensor.2d.shared::cluster.global.mbarrier::complete_tx::bytes [%0+5120],[%1,{%2,%5}],[%4];}"
               ::"r"(dst), "l"(m), "r"(slot * 64), "r"(half * 80), "r"(mb), "r"(half * 80 + 40) : "memory");
}
__device__ __forceinline__ uint4 exch_b128(void* p, uint32_t x, uint32_t y, uint32_t z, uint32_t w) {
  uint4 v;
  asm volatile("{.reg .b128 s, t; .reg .b64 a,b; mov.b64 a,{%5,%6}; mov.b64 b,{%7,%8}; mov.b128 s,{a,b}; atom.relaxed.gpu.global.exch.b128 t,[%4],s;"
               " mov.b128 {a,b},t; mov.b64 {%0,%1},a; mov.b64 {%2,%3},b;}" : "=r"(v.x), "=r"(v.y), "=r"(v.z), "=r"(v.w) : "l"(p), "r"(x), "r"(y), "r"(z), "r"(w) : "memory");
  return v;
}
#define CONSUME(v) do { if ((v) == 0x7fc12345u) sts1(sb + rec::BARS + 96, 0); } while (0)
__device__ __forceinline__ uint2 ldg_b64(const void* p) { uint2 v; asm volatile("{.reg .b64 t; ld.relaxed.gpu.global.b64 t,[%2]; mov.b64 {%0,%1},t;}" : "=r"(v.x), "=r"(v.y) : "l"(p) : "memory"); return v; }
__device__ __forceinline__ void stg_b64(void* p, uint32_t x, uint32_t y) { asm volatile("{.reg .b64 t; mov.b64 t,{%1,%2}; st.relaxed.gpu.global.b64 [%0],t;}" ::"l"(p), "r"(x), "r"(y) : "memory"); }
__device__ __forceinline__ uint32_t tagbad(uint32_t x, uint32_t y, uint32_t tag) { uint32_t r; asm("lop3.b32 %0,%1,%2,%3,0x7e;" : "=r"(r) : "r"(x), "r"(y), "r"(tag)); return r; }

__device__ __forceinline__ bool anybad(uint32_t a, uint32_t b, uint32_t c, uint32_t d, uint32_t e, uint32_t f, uint32_t g, uint32_t h, uint32_t tag) {
  uint32_t r;
  asm volatile("{.reg .b32 t,u,v,w; .reg .pred p; lop3.b32 t,%1,%2,%9,0x7e; lop3.b32 u,%3,%4,%9,0x7e; lop3.b32 v,%5,%6,%9,0x7e; lop3.b32 w,%7,%8,%9,0x7e;"
               " lop3.b32 t,t,u,v,0xfe; lop3.b32 t,t,w,1,0xa8; setp.ne.u32 p,t,0; vote.sync.any.pred p,p,0xffffffff; selp.u32 %0,1,0,p;}"
               : "=r"(r) : "r"(a), "r"(b), "r"(c), "r"(d), "r"(e), "r"(f), "r"(g), "r"(h), "r"(tag));
  return r;
}
__device__ __forceinline__ bool anybad(uint32_t a, uint32_t b, uint32_t c, uint32_t d, uint32_t tag) {
  uint32_t r;
  asm volatile("{.reg .b32 t,u; .reg .pred p; lop3.b32 t,%1,%2,%5,0x7e; lop3.b32 u,%3,%4,%5,0x7e;"
               " lop3.b32 t,t,u,1,0xa8; setp.ne.u32 p,t,0; vote.sync.any.pred p,p,0xffffffff; selp.u32 %0,1,0,p;}"
               : "=r"(r) : "r"(a), "r"(b), "r"(c), "r"(d), "r"(tag));
  return r;
}
#define BADS(r) anybad(r[0].x, r[0].y, r[1].x, r[1].y, r[2].x, r[2].y, r[3].x, r[3].y, tag)
constexpr float SCS = 0.08838834764831845f * 1.4426950408889634f / 16.f;
__device__ __forceinline__ uint32_t pkh(float lo, float hi, uint32_t tag) {
  uint32_t r;
  asm("{.reg .b32 t; cvt.rn.satfinite.f16x2.f32 t,%1,%2; lop3.b32 %0,t,0xfffffffe,%3,0xea;}" : "=r"(r) : "f"(hi), "f"(lo), "r"(tag));
  return r;
}
__device__ __forceinline__ uint32_t addh(uint32_t a, uint32_t b) { uint32_t r; asm("add.rn.f16x2 %0,%1,%2;" : "=r"(r) : "r"(a), "r"(b)); return r; }
__device__ __forceinline__ float hlo(uint32_t v) { float r; asm("{.reg .b16 a,b; mov.b32 {a,b},%1; cvt.f32.f16 %0,a;}" : "=f"(r) : "r"(v)); return r; }
__device__ __forceinline__ float hhi(uint32_t v) { float r; asm("{.reg .b16 a,b; mov.b32 {a,b},%1; cvt.f32.f16 %0,b;}" : "=f"(r) : "r"(v)); return r; }
__device__ __forceinline__ uint32_t ordh(uint32_t v) {
  uint32_t r;
  asm("{.reg .b32 m; prmt.b32 m,%1,0,0xbb99; lop3.b32 %0,%1,m,0x7fff7fff,0x78;}" : "=r"(r) : "r"(v));
  return r;
}
template <bool MASK>
__device__ __forceinline__ float4 softmax2(const uint2 (&r)[4], uint32_t mx, uint32_t my) {
  uint32_t x = addh(addh(r[0].x, r[1].x), addh(r[2].x, r[3].x)), y = addh(addh(r[0].y, r[1].y), addh(r[2].y, r[3].y)), k;
  if (MASK) x = addh(x, mx);
  y = addh(y, my);
  asm("max.f16x2 %0,%1,%2;" : "=r"(k) : "r"(x), "r"(y));
  k = ordh(k);
  const int k0 = __reduce_max_sync(~0u, (int)(k << 16)), k1 = __reduce_max_sync(~0u, (int)k);
  k = ordh(__byte_perm(k0, k1, 0x7632));
  const float m0 = hlo(k) * -16.f, m1 = hhi(k) * -16.f;
  return make_float4(ex2(fmaf(hlo(x), 16.f, m0)), ex2(fmaf(hhi(x), 16.f, m1)), ex2(fmaf(hlo(y), 16.f, m0)), ex2(fmaf(hhi(y), 16.f, m1)));
}
__device__ __forceinline__ char* mkp(uint32_t lo, uint32_t hi) { uint64_t r; asm("mov.b64 %0,{%1,%2};" : "=l"(r) : "r"(lo), "r"(hi)); return (char*)r; }
#define LO(p) ((uint32_t)(uint64_t)(p))
#define HI(p) ((uint32_t)((uint64_t)(p) >> 32))
__device__ __forceinline__ uint32_t addbf(uint32_t a, uint32_t b) { uint32_t r; asm("add.rn.bf16x2 %0,%1,%2;" : "=r"(r) : "r"(a), "r"(b)); return r; }
__device__ __forceinline__ void pv_mem(const uint32_t (&p)[4], uint32_t pm, const uint4 (&v)[4], const uint4 (&vn)[2], uint32_t (&O)[4], uint32_t sums, uint32_t l16) {
  float o[4][4] = {{0, 0, 0, 0}, {0, 0, 0, 0}, {0, 0, 0, 0}, {0, 0, 0, 0}}, sum[4] = {0, 0, 0, 0};
  const uint32_t one = 0x3f803f80u;
  mma8(sum, one, one, pm);
  mma16(o[0], v[0].x, v[0].y, v[0].z, v[0].w, p[0], p[1]);
  mma16(o[1], v[2].x, v[2].y, v[2].z, v[2].w, p[0], p[1]);
  mma16(o[2], v[1].x, v[1].y, v[1].z, v[1].w, p[2], p[3]);
  mma16(o[3], v[3].x, v[3].y, v[3].z, v[3].w, p[2], p[3]);
  mma16(sum, one, one, one, one, p[0], p[1]);
  mma16(o[0], vn[0].x, vn[0].y, vn[0].z, vn[0].w, pm, pm);
  mma16(o[1], vn[1].x, vn[1].y, vn[1].z, vn[1].w, pm, pm);
  {
    mma16(sum, one, one, one, one, p[2], p[3]);
    asm volatile("{.reg .pred p; .reg .b32 t; and.b32 t,%3,0x1c0; setp.eq.u32 p,t,0; @p st.shared.v2.f32 [%0],{%1,%2};}" ::"r"(sums), "f"(sum[0]), "f"(sum[1]), "r"(l16) : "memory");
  }
  O[0] = pk(o[0][0] + o[2][0], o[0][1] + o[2][1]); O[1] = pk(o[0][2] + o[2][2], o[0][3] + o[2][3]);
  O[2] = pk(o[1][0] + o[3][0], o[1][1] + o[3][1]); O[3] = pk(o[1][2] + o[3][2], o[1][3] + o[3][3]);
}
__device__ __forceinline__ void pv_tok(const uint32_t (&p)[4], uint32_t pm, const uint4 (&v)[4], const uint32_t (&vm)[4], uint32_t (&O)[4]) {
  float o[2][4] = {{0, 0, 0, 0}, {0, 0, 0, 0}}, sum[4] = {0, 0, 0, 0};
  const uint32_t one = 0x3f803f80u;
  mma16(sum, one, one, one, one, p[0], p[1]);
  mma16(o[0], v[0].x, v[0].y, v[0].z, v[0].w, p[0], p[1]);
  mma16(o[1], v[2].x, v[2].y, v[2].z, v[2].w, p[0], p[1]);
  mma16(sum, one, one, one, one, p[2], p[3]);
  mma16(o[0], v[1].x, v[1].y, v[1].z, v[1].w, p[2], p[3]);
  mma16(o[1], v[3].x, v[3].y, v[3].z, v[3].w, p[2], p[3]);
  mma8(sum, one, one, pm);
  mma8(o[0], vm[0], vm[1], pm);
  mma8(o[1], vm[2], vm[3], pm);
  float i0, i1;
  asm("rcp.approx.ftz.f32 %0,%1;" : "=f"(i0) : "f"(sum[0]));
  asm("rcp.approx.ftz.f32 %0,%1;" : "=f"(i1) : "f"(sum[1]));
  O[0] = pk(o[0][0] * i0, o[0][1] * i1); O[1] = pk(o[0][2] * i0, o[0][3] * i1);
  O[2] = pk(o[1][0] * i0, o[1][1] * i1); O[3] = pk(o[1][2] * i0, o[1][3] * i1);
}
template <int OFF>
__device__ __forceinline__ void sta1(uint32_t a, uint32_t v, uint32_t mb) {
  asm volatile("st.async.shared::cluster.mbarrier::complete_tx::bytes.b32 [%0+%3],%1,[%2];" ::"r"(a), "r"(v), "r"(mb), "n"(OFF) : "memory");
}

__device__ __forceinline__ void rec_helper(char* smem, const bf16* x, const bf16* cvec, const CUtensorMap* wm) {
  const int tid = threadIdx.x, hb = blockIdx.x & 3;
  float4* md = (float4*)(smem + 12288);
  uint4* hs = (uint4*)(smem + 152 * 1024);
  uint4 xr[8];
  const uint4* px = (const uint4*)(x + (size_t)(hb * 16 + (tid >> 5) * 2) * 1024) + (tid & 31);
#pragma unroll
  for (int i = 0; i < 8; i++) xr[i] = __ldg(px + i * 32);
#pragma unroll 1
  for (int i = tid; i < 2560; i += 256) g_ar[hb * 2560 + i] = make_uint4(0, 0, 0, 0);
  g_tm[tid] = 0;
  g_oc[hb * 256 + tid] = 0;
  float4 mr[16];
#pragma unroll 1
  for (int k = 0; k < 32; k++) {
    float v[2][32], m[8] = {}, q[8] = {};
#pragma unroll
    for (int i = 0; i < 8; i++) {
      const uint4 u = xr[i];
      float* w = v[i >> 2] + (i & 3) * 8;
      w[0] = blo(u.x); w[1] = bhi(u.x); w[2] = blo(u.y); w[3] = bhi(u.y); w[4] = blo(u.z); w[5] = bhi(u.z); w[6] = blo(u.w); w[7] = bhi(u.w);
      xr[i] = __ldg(px + min(k + 1, 31) * 8192 + i * 32);
    }
#pragma unroll
    for (int i = 0; i < 64; i++) m[i & 7] += v[i & 1][i >> 1];
    m[0] = (m[0] + m[2]) + (m[4] + m[6]); m[1] = (m[1] + m[3]) + (m[5] + m[7]);
#pragma unroll
    for (int o = 16; o; o >>= 1) { m[0] += __shfl_xor_sync(~0u, m[0], o); m[1] += __shfl_xor_sync(~0u, m[1], o); }
    m[0] *= 1.f / 1024; m[1] *= 1.f / 1024;
#pragma unroll
    for (int i = 0; i < 64; i++) { float& w = v[i & 1][i >> 1]; w -= m[i & 1]; q[i & 7] += w * w; }
    q[0] = (q[0] + q[2]) + (q[4] + q[6]); q[1] = (q[1] + q[3]) + (q[5] + q[7]);
#pragma unroll
    for (int o = 16; o; o >>= 1) { q[0] += __shfl_xor_sync(~0u, q[0], o); q[1] += __shfl_xor_sync(~0u, q[1], o); }
    const float rstd[2] = {rsqrtf(q[0] * (1.f / 1024) + 1e-5f), rsqrtf(q[1] * (1.f / 1024) + 1e-5f)};
    if (k == 0) {
      PT(44);
#pragma unroll 1
      for (int i = 0; i < 2; i++) {
        uint4 p[4];
        int it = 0;
        while (true) {
#pragma unroll
          for (int u = 0; u < 4; u++) p[u] = ldg_rlx4(g_modp + u * 512 + i * 256 + tid);
          uint32_t ok = 1;
#pragma unroll
          for (int u = 0; u < 4; u++) ok &= p[u].x & p[u].y & p[u].z & p[u].w;
          if (__all_sync(~0u, ok)) break;
          if (++it > SPIN_LIMIT) __trap();
          __nanosleep(100);
        }
        md[i * 256 + tid] = make_float4(i + rbf((F_(p[0].x) + F_(p[1].x)) + (F_(p[2].x) + F_(p[3].x))), i + rbf((F_(p[0].y) + F_(p[1].y)) + (F_(p[2].y) + F_(p[3].y))),
                                        i + rbf((F_(p[0].z) + F_(p[1].z)) + (F_(p[2].z) + F_(p[3].z))), i + rbf((F_(p[0].w) + F_(p[1].w)) + (F_(p[2].w) + F_(p[3].w))));
      }
      BAR_SYNC(rec::B_F, 256);
#pragma unroll
      for (int i = 0; i < 16; i++) mr[i] = md[(i >> 3) * 256 + ((i >> 1) & 3) * 64 + (tid & 31) * 2 + (i & 1)];
      PT(45);
    }
#pragma unroll
    for (int i = 0; i < 4; i++) {
      const int ch = i * 32 + (tid & 31);
      const float4 s0 = mr[i * 2], s1 = mr[i * 2 + 1], c0 = mr[8 + i * 2], c1 = mr[9 + i * 2];
#pragma unroll
      for (int r = 0; r < 2; r++) {
        const int row = (tid >> 5) * 2 + r;
        const float* w = v[r] + i * 8;
        hs[(k & 1) * 2048 + (ch >> 3) * 128 + row * 8 + ((ch & 7) ^ (row & 7))] =
            make_uint4(pk(w[0] * rstd[r] * c0.x + s0.x, w[1] * rstd[r] * c0.y + s0.y), pk(w[2] * rstd[r] * c0.z + s0.z, w[3] * rstd[r] * c0.w + s0.w),
                       pk(w[4] * rstd[r] * c1.x + s1.x, w[5] * rstd[r] * c1.y + s1.y), pk(w[6] * rstd[r] * c1.z + s1.z, w[7] * rstd[r] * c1.w + s1.w));
      }
    }
    if (k == 0) PT(63);
    FENCE_ASYNC_SMEM();
    BAR_SYNC(rec::B_W, 288);
    if (k < 2) PT(46 + k * 12);
  }
  PT(59);
  PDUMP();
  const uint32_t sc = (uint32_t)__cvta_generic_to_shared(smem), wb = sc + 20480, mb = sc + rec::PACE;
#pragma unroll 1
  for (int i = tid; i < 512; i += 256) sts1(sc + i * 4, pk(silu(__bfloat162float(cvec[2 * i])), silu(__bfloat162float(cvec[2 * i + 1]))));
#pragma unroll 1
  for (int i = tid; i < 2048; i += 256) g_stat[hb * 2048 + i] = make_uint4(~0u, ~0u, ~0u, ~0u);
#pragma unroll 1
  for (int i = tid; i < 512; i += 256) g_cnt[hb * 512 + i] = 0;
  if (tid == 0 && hb == 0) g_fcnt = 0;
  if (tid == 0) asm volatile("{.reg .u32 t; mov.u32 t,%%smid; st.global.u32 [%0],t;}" ::"l"((unsigned*)g_hsm + hb) : "memory");
  BAR_SYNC(rec::B_O, 320);
  if (tid == 0) FT(37);
  const int lane = tid & 31;
  const uint32_t fa = wb + (tid >> 5) * 8192 + ((lane & 7) + (lane >> 4) * 8) * 128 + ((((lane >> 3) & 1) ^ (lane & 7)) << 4);
  float acc[2][4][4] = {};
#pragma unroll 1
  for (int i2 = -2; i2 < 32; i2 += 2) {
#pragma unroll
    for (int u = 0; u < 2; u++) {
      const int i = i2 + u;
      if (i < 30 && tid < 32) e_expect_tma3d<true>(wb + (i + 2) % 3 * 65536, wm, (i2 + 2) * 32, 32 + hb * 16 + u * 8, mb + (i + 2) % 3 * 8, 65536);
      if (i < 0) continue;
      mbar_wait(mb + i % 3 * 8, i / 3 & 1);
#pragma unroll
      for (int ks = 0; ks < 4; ks++) {
        const uint32_t b0 = lds1(sc + i2 * 64 + ks * 32 + (lane & 3) * 4), b1 = lds1(sc + i2 * 64 + ks * 32 + (lane & 3) * 4 + 16);
#pragma unroll
        for (int m = 0; m < 4; m++) {
          uint32_t a[4];
          ldsm4t(a, (fa ^ (m * 32)) + i % 3 * 65536 + ks * 2048);
          mma16(acc[u][m], a[0], a[1], a[2], a[3], b0, b1);
        }
      }
      FENCE_ASYNC_SMEM();
      BAR_SYNC(rec::B_F, 256);
    }
  }
  if (!(lane & 3)) {
#pragma unroll
    for (int i = 0; i < 16; i++) g_mod[2048 + hb * 1024 + (i >> 3) * 512 + (tid >> 5) * 64 + (i & 7) * 8 + (lane >> 2)] = rbf(acc[i >> 3][(i >> 1) & 3][(i & 1) * 2]);
  }
  BAR_SYNC(rec::B_F, 256);
  if (tid == 0) asm volatile("fence.acq_rel.gpu; griddepcontrol.launch_dependents;" ::: "memory");
  if (tid == 0) FT(33);
}

__global__ void __cluster_dims__(2, 1, 1) __launch_bounds__(512, 1)
k_rec(const __grid_constant__ RecMaps mp, const bf16* __restrict__ mem0, const bf16* __restrict__ x, const bf16* __restrict__ cvec,
      const bf16* __restrict__ wmod, const bf16* __restrict__ wo_g, char* xc, int dF, int dA, int dS, int dM, int dG, int dP, int dX, int dD, int dZ, int dZ2, int dV, int dX2) {
  using namespace rec;
  extern __shared__ __align__(1024) char smem[];
  const uint32_t sb = (uint32_t)__cvta_generic_to_shared(smem);
  if ((sb & 0x3FFFF) != 1024) __trap();
  PH(0);
  PZERO();
  if (threadIdx.x == 0) {
    int b = blockIdx.x;
    if (b >= 8 && b < 128) {
      const int t = (b >> 1) - 4, u = t - 32;
      b = 2 * (t < 32 ? 4 + (t & 16) + (t & 7) * 2 + ((t >> 3) & 1) : 36 + (u / 14) * 14 + (u % 7) * 2 + ((u / 7) & 1)) + (b & 1);
    }
    sts1(sb + rec::PACE + 24, b);
  }
#define ROLE_REFRESH { asm volatile("mov.u32 %0,%%tid.x;" : "=r"(tid)); wid = __shfl_sync(~0u, tid >> 5, 0); b = __shfl_sync(~0u, lds1(sb + PACE + 24), 0); }
#define ROLE_VARS int tid; asm volatile("mov.u32 %0,%%tid.x;" : "=r"(tid)); \
    int wid = __shfl_sync(~0u, tid >> 5, 0), b = __shfl_sync(~0u, lds1(sb + PACE + 24), 0);
#define wg (wid >> 2)
#define iw (wid & 3)
#define h (b >> 2)
#define j (b & 3)
#define a (b & 1)
#define bb ((b >> 1) & 1)
  const uint32_t wbar = sb + BARS + 48, obar = wbar + 8;
  if (threadIdx.x == 256) {
    for (int i = 0; i < 18; i++) if (i != 12) mbar_init(sb + BARS + i * 8, i == 3 || i == 8 || i == 9 || i == 10 ? 2 : 1);
    for (int i = 0; i < 3; i++) mbar_init(sb + PACE + i * 8, 1);
    asm volatile("fence.mbarrier_init.release.cluster;" ::: "memory");
    FENCE_ASYNC_SMEM();
    mbar_expect(sb + BARS, 2048);
    mbar_expect(sb + BARS + 16, 4096);
    mbar_expect(sb + BARS + 32, 4096);
    mbar_expect(sb + BARS + 40, 4096);
  }
  __syncthreads();
#define lane ((int)(l16 >> 4))
#define l16 (L16 & 0x1f0)
#define PIN(x) __shfl_xor_sync(~0u, (uint32_t)(x), 0)
#define lpub ((L16 & 0x30) * 64 + ((L16 >> 3) & 0x38))
#define lrow ((L16 & 0x70) + (((L16 >> 3) ^ L16) & 0x70 & ~((L16 >> 3) & 0x40) ? L16 & 0x180 : 512))

  const int role = __shfl_sync(~0u, threadIdx.x >> 7, 0);
  if (role < 2) {
    asm volatile("setmaxnreg.inc.sync.aligned.u32 %0;" ::"n"(RF_));
    if (blockIdx.x >= 128) { rec_helper(smem, x, cvec, &mp.wm3); return; }
    ROLE_VARS
    uint32_t L16 = __shfl_sync(~0u, sb + (tid & 31) * 16, tid & 31);
    {
      uint4 wm[8];
      const uint4* pw = (const uint4*)(wmod + (size_t)((b >> 5) * 256 + (tid >> 3)) * 6144 + (b & 31) * 64) + (tid & 7);
      const float cs = __bfloat162float(cvec[(b >> 5) * 256 + tid]);
#pragma unroll
      for (int i = 0; i < 8; i++) wm[i] = __ldcs(pw + (size_t)i * 32 * 768);
      float* sc = (float*)(smem + PRE);
      sc[tid] = rbf(silu(cs));
      BAR_SYNC(B_F, 256);
      PT(42);
      float acc[8] = {0, 0, 0, 0, 0, 0, 0, 0};
#pragma unroll
      for (int i = 0; i < 8; i++) {
        const float f = sc[i * 32 + (tid >> 3)];
        acc[0] += f * blo(wm[i].x); acc[1] += f * bhi(wm[i].x); acc[2] += f * blo(wm[i].y); acc[3] += f * bhi(wm[i].y);
        acc[4] += f * blo(wm[i].z); acc[5] += f * bhi(wm[i].z); acc[6] += f * blo(wm[i].w); acc[7] += f * bhi(wm[i].w);
      }
#pragma unroll
      for (int i = 0; i < 8; i++) { acc[i] += __shfl_xor_sync(~0u, acc[i], 8); acc[i] += __shfl_xor_sync(~0u, acc[i], 16); }
      float* red = sc + 256;
      if ((tid & 31) < 8) {
#pragma unroll
        for (int i = 0; i < 8; i++) red[(tid >> 5) * 64 + (tid & 7) * 8 + i] = acc[i];
      }
      BAR_SYNC(B_F, 256);
      if (tid < 64) {
        float t = 0;
#pragma unroll
        for (int i = 0; i < 8; i++) t += red[i * 64 + tid];
        asm volatile("st.relaxed.gpu.global.u32 [%0],%1;" ::"l"((unsigned*)g_modp + (b >> 5) * 2048 + (b & 31) * 64 + tid), "r"(U_(t) | 1u) : "memory");
      }
      PH(1); PT(43);
    }
    uint32_t m0[2][4];
#pragma unroll
    for (int i = 0; i < 2; i++)
#pragma unroll
      for (int r = 0; r < 4; r++)
        m0[i][r] = (uint32_t)__bfloat16_as_ushort(mem0[(2 * r) * 1024 + a * 512 + tid * 2 + i]) | ((uint32_t)__bfloat16_as_ushort(mem0[(2 * r + 1) * 1024 + a * 512 + tid * 2 + i]) << 16);
    ROLE_REFRESH
    uint32_t wQ[16][4], wK[16][4], wV[NVR][4];
    uint32_t frag = sb + ((lane & 7) + (lane >> 4) * 8) * 128 + (((iw * 2 + ((lane >> 3) & 1)) ^ (lane & 7)) << 4);
    mbar_wait(wbar, 0);
    PH(2); PT(48);
#pragma unroll
    for (int i = 0; i < 16; i++) { ldsm4t(wQ[i], frag + WO + wg * 32768 + i * 2048); ldsm4t(wK[i], frag + XB + wg * 32768 + i * 2048); }
    FENCE_ASYNC_SMEM();
    PH(3); PT(49);
    CLUSTER_SYNC();
    PT(50);
    auto x_load = [&](int n) {
      asm volatile("{.reg .pred p; elect.sync _|p, 0xffffffff; @p mbarrier.arrive.expect_tx.shared.b64 _,[%2],32768;\n"
                   "@p cp.async.bulk.shared::cluster.global.mbarrier::complete_tx::bytes [%0],[%1],32768,[%2];}"
                   ::"r"(sb + (X1 && n ? WO : XB)), "l"(g_h + n * 4096 + a * 2048), "r"(sb + BARS + (X1 && n ? 120 : 136)) : "memory");
    };
    if (wid == 0) {
      wait_h(0);
      PT(47);
      x_load(0);
      if (X1) { wait_until(clk(), XD1); x_load(1); }
    }
#define owner ((iw >> 1) == a)
#define oi (wid & 1)
    frag += wg * NVS * 2048;
    {
      const uint32_t rsb = mapa(sb, iw >> 1);
      const uint32_t pp = rsb + PK + (owner ? 0 : 12288) + (oi * 2048 + wg * 1024) + l16;
      const uint32_t mb = sb + MEM + wg * 5120;
      const uint32_t t = sb + TF + wid * TFP + lane * 4;
      sts1(t + T_MEM, mb + lrow);
      sts1(t + T_QK, owner ? L16 + (lane >> 4) * (RK - RQ - 256) + RQ + oi * 1024 + wg * 256 : rsb + RQ + oi * 1024 + 512 + wg * 256 + (l16 >> 2));
      sts1(t + T_O, L16 + OB);
      sts1(t + T_WV, frag);
      sts1(t + T_WO, sb + WO + (wid >> 1) * 16384 + ((lane & 7) + (lane >> 4) * 8) * 128 + ((((wid & 1) * 4 + ((lane >> 3) & 1)) ^ (lane & 7)) << 4));
      sts1(t + T_AR, sb + ARO + wid * 640 + lrow);
      sts1(t + T_PK, pp);
      sts1(t + T_VM, LO(xc) + h * 262144 + (bb * 2 + (iw >> 1)) * XC + X_VM(0) + oi * 2048 + a * 256 + (l16 >> 1));
      sts1(t + T_RX, L16 + RX + iw * 512);
    }
    uint32_t tp = sb + TF + wid * TFP + lane * 4;
    if (!wg) {
      const uint32_t xo = lds1(tp + T_VM);
      stg_b64(mkp(xo, HI(xc)), 0, 0); stg_b64(mkp(xo + X_RING, HI(xc)), 0, 0);
    }
    int wo_ = __shfl_sync(~0u, owner + wg * 2, 0);
    auto park_ptr = [&]() { return lds1(tp + T_PK); };
    auto park = [&](const float* f, int m, int n, uint32_t d) {
      uint32_t w[8];
#pragma unroll
      for (int i = 0; i < 8; i++) w[i] = pk(f[2 * i], f[2 * i + 1]);
      if (wo_ & 1) {
        sts4(d + m * 4096, w[0], w[1], w[2], w[3]); sts4(d + m * 4096 + 512, w[4], w[5], w[6], w[7]);
      } else {
        const uint32_t pb = (d & 0xff000000u) + 1024 + BARS + (m ? 24 + m * 8 : 16);
        {
          sta4(d + m * 4096, w, pb); sta4(d + m * 4096 + 512, w + 4, pb);
        }
      }
    };
    auto xdesc = [&](int n) { return mkdesc(__shfl_sync(~0u, 1024 + (X1 && n == 1 ? WO : XB) + wg * 16384, 0), 16, 1024); };
    uint64_t xpre = 0;
    auto rs_issue = [&](float* acc, const uint32_t (&w)[16][4], int n, bool fence, bool pre = false) {
      const uint64_t x = pre ? xpre : xdesc(n);
      if (fence) WG_FENCE();
      wgmma_rs_n32_z(acc, w[0], x);
#pragma unroll
      for (int i = 1; i < 16; i++) wgmma_rs_n32(acc, w[i], x + (i >> 2) * 256 + (i & 3) * 2, 1);
      WG_COMMIT();
    };
    auto v_issue = [&](float* acc, int n, bool fence) {
      const uint64_t dv = mkdesc(__shfl_sync(~0u, 1024 + WVS + wg * NVS * 2048, 0), 16, 1024), x = xdesc(n);
      if (fence) WG_FENCE();
      wgmma_rs_n32_z(acc, wV[0], x);
#pragma unroll
      for (int i = NVR; i < 16; i++) wgmma_ssT_n32(acc, dv + (i - NVR) * 128, x + (i >> 2) * 256 + (i & 3) * 2, 1);
#pragma unroll
      for (int i = 1; i < NVR; i++) wgmma_rs_n32(acc, wV[i], x + (i >> 2) * 256 + (i & 3) * 2, 1);
      WG_COMMIT();
    };
    uint32_t mA;
    auto vk_pass = [&](int n, uint32_t d, bool pro) {
      float acc[16], acc2[16];
      if (VW) rs_issue(acc, wQ, pro ? n : 0, true); else v_issue(acc, pro ? n : 0, true);
      rs_issue(acc2, wK, pro ? n : 0, false);
      if (n > 0) mbar_wait(sb + BARS + 80, (n - 1) & 1);
      WG_WAIT(1);
      park(acc, 2, n, d);
      mA = lds1(tp + T_MEM);
      BAR_ARRIVE(B_K, 320);
      WG_WAIT(0);
      park(acc2, 1, n, d);
    };
    auto wo_load = [&](int i0, int i1) {
      if (i1 == 4) asm volatile("{.reg .pred p; elect.sync _|p, 0xffffffff; @p mbarrier.arrive.expect_tx.shared.b64 _,[%0],65536;}" ::"r"(obar) : "memory");
#pragma unroll
      for (int i = i0; i < i1; i++)
        asm volatile("{.reg .pred p; elect.sync _|p, 0xffffffff; @p cp.async.bulk.tensor.2d.shared::cluster.global.mbarrier::complete_tx::bytes [%0],[%1,{%2,%3}],[%4];}"
                     ::"r"(sb + WO + i * 16384), "l"(&mp.wo), "r"(j * 256 + i * 64), "r"(h * 128), "r"(obar) : "memory");
    };
    {
#pragma unroll 1
      for (int n = 0; n < 2; n++) {
        float acc[16];
        asm volatile("" : "+r"(wid), "+r"(wo_));
        if (X1) mbar_wait(sb + BARS + 136 - n * 16, 0); else mbar_wait(sb + BARS + 136, n);
        PT(51 + n * 3);
        if (!X1 && n == 1 && wid == 0) wo_load(0, 4);
        if (X1 && n == 1 && wid == 0) wo_load(2, 4);
        if (!VW) {
          rs_issue(acc, wQ, n, true);
          if (n > 0) mbar_wait(sb + BARS + 24, 0);
          WG_WAIT(0);
          park(acc, 0, n, park_ptr());
        }
        if (!n) {
          mbar_wait(sb + BARS + 88, 0);
          PT(60);
#pragma unroll
          for (int i = 0; i < NVR; i++) ldsm4t(wV[i], frag + MEM + (wg * (NVR - NVS) + i) * 2048);
          BAR_SYNC(B_H, 256);
#pragma unroll
          for (int i = 0; i < 2; i++) {
            const int k = tid * 2 + i, m = (k >> 3) & 3, r = k & 7;
            sts4(sb + MEM + (k >> 5) * 640 + (r == m ? 512 : m * 128) + r * 16, m0[i][0], m0[i][1], m0[i][2], m0[i][3]);
          }
          if (lane < 8) {
            sts4(sb + ARO + wid * 640 + (lane < 4 ? lane * 144 : 512 + l16), 0x3f803f80, 0x3f803f80, 0x3f803f80, 0x3f803f80);
#pragma unroll
            for (int i = 0; i < 2; i++) sts4(sb + MEM + (wid * 2 + i) * 640 + (lane < 4 ? lane * 144 : 512 + l16), 0x42004200, 0x42004200, 0x42004200, 0x42004200);
          }
        }
        if (VW) {
          v_issue(acc, n, true);
          if (n > 0) mbar_wait(sb + BARS + 24, 0);
          if (X1 && n > 0) BAR_SYNC(B_H, 320);
          WG_WAIT(0);
          park(acc, 0, n, park_ptr());
        }
        PT(52 + n * 3);
        BAR_ARRIVE(B_C, 320);
        vk_pass(n, park_ptr(), true);
        PT(53 + n * 3);
        if (n > 0) break;
        BAR_ARRIVE(B_X, 320);
        if (X1) { BAR_ARRIVE(B_Q, 288); continue; }
        BAR_SYNC(B_H, 256);
        if (wid == 0) x_load(1);
        BAR_SYNC(B_C, 320);
      }
      BAR_ARRIVE(B_P, 384); BAR_ARRIVE(B_X, 320);
      if (!X1) BAR_ARRIVE(B_Q, 288);
      BAR_SYNC(B_T0, 320);
      if (X1 && wid == 0) wo_load(0, 2);
    }
    PH(4);
    PT(57);
    ROLE_REFRESH
    for (int s = 0; s < 64; s++) {
      asm volatile("" : "+r"(tp), "+r"(wo_));
      wid = wo_ * 2;
      uint32_t vS[NVS][4], bf[8][4], rm;
      if (s > 0) BAR_SYNC(B_R, 320);
#define VMMA(c, w, i) mma16(c, (w)[0], (w)[1], (w)[2], (w)[3], bf[(i) >> 1][((i) & 1) * 2], bf[(i) >> 1][((i) & 1) * 2 + 1])
      {
        float cQ[4] = {0, 0, 0, 0}, cK[4] = {0, 0, 0, 0}, dQ[4] = {0, 0, 0, 0}, dK[4] = {0, 0, 0, 0};
#pragma unroll
        for (int t = 7; t >= 8 - NB1; t--) ldsm4t(bf[t], mA + t * 640);
        SCHED_FENCE(47);
#pragma unroll
        for (int i = 15; i >= 0; i--) {
          if (i & 1) { VMMA(dQ, wQ[i], i); VMMA(dK, wK[i], i); } else { VMMA(cQ, wQ[i], i); VMMA(cK, wK[i], i); }
          if (i == 0) {
#pragma unroll
            for (int e = 0; e < 4; e++) { cQ[e] += dQ[e]; cK[e] += dK[e]; }
          }
          if (i == IB2 && NB2) {
            SCHED_FENCE(49);
#pragma unroll
            for (int t = 7 - NB1; t >= 8 - NB1 - NB2; t--) ldsm4t(bf[t], mA + t * 640);
          }
          if (i == IB3) {
            if (NB1 + NB2 < 8) SCHED_FENCE(51);
#pragma unroll
            for (int t = 7 - NB1 - NB2; t >= 0; t--) ldsm4t(bf[t], mA + t * 640);
            rm = lds1(tp + T_QK); frag = lds1(tp + T_WV);
          }
          if (i == IV) {
#pragma unroll
            for (int u = 0; u < NVP; u++) ldsm4t(vS[NVS - 1 - u], frag + WVS + (NVS - 1 - u) * 2048);
          }
        }
        const uint32_t w0 = pk(cQ[0] * SCS, cQ[1] * SCS), w1 = pk(cQ[2] * SCS, cQ[3] * SCS), w2 = pk(cK[0], cK[1]), w3 = pk(cK[2], cK[3]);
        if (wo_ & 1) {
          stsm4(rm, w0, w1, w2, w3);
          BAR_ARRIVE(B_E, 256);
        } else {
          const uint32_t mm = (rm & 0xff000000u) + 1024 + BARS;
          sta1<0>(rm, w0, mm); sta1<128>(rm, w1, mm);
          sta1<RK - RQ>(rm, w2, mm); sta1<RK - RQ + 128>(rm, w3, mm);
        }
        if (tp - sb - TF < 3 * TFP && tp - sb - TF >= 2 * TFP) TS(0);
      }
      uint32_t oA, woA;
      {
        float cV[4] = {0, 0, 0, 0}, cW[4] = {0, 0, 0, 0};
        static_assert(NVP == 2 && NVR == 5, "schedule");
#define VLD(k) ldsm4t(vS[(k) - NVR], frag + WVS + ((k) - NVR) * 2048)
#define VS_(c, k) VMMA(c, vS[(k) - NVR], k)
        const uint32_t ex = lds1(tp + T_RX), xv = lds1(tp + T_VM);
        VLD(13);
        VS_(cW, 15); VS_(cV, 14); VLD(12); VLD(11); VMMA(cW, wV[4], 4); VMMA(cV, wV[3], 3); VLD(10); VMMA(cW, wV[2], 2); VLD(9);
        VMMA(cV, wV[1], 1); VLD(8); VMMA(cW, wV[0], 0); VLD(7); VS_(cV, 13); VLD(6); VS_(cW, 12); VLD(5);
        VS_(cV, 11); VS_(cW, 10); VS_(cV, 9); VS_(cW, 8); VS_(cV, 7); VS_(cW, 6); VS_(cV, 5);
#pragma unroll
        for (int e = 0; e < 4; e++) cV[e] += cW[e];
        woA = lds1(tp + T_WO);
        oA = lds1(tp + T_O + (s & dZ));
        if (wg) {
          sts4(ex, U_(cV[0]), U_(cV[1]), U_(cV[2]), U_(cV[3]));
          BAR_ARRIVE(B_T2, 256);
        } else {
          BAR_SYNC(B_T2, 256);
          const float4 u = lds4f(ex);
          stg_b64(mkp(xv ^ ((s & 1) * X_RING), HI(xc)), (pk(cV[0] + u.x, cV[1] + u.y) & ~1u) | (((s >> 1) + 1) & 1), pk(cV[2] + u.z, cV[3] + u.w));
        }
      }
      if (s == 63) break;
      {
        mbar_wait(obar, 0);
        const uint32_t woB = woA ^ 32;
        uint32_t wo[16][4];
#pragma unroll
        for (int i = 0; i < NW1; i++) ldsm4t(wo[i], ((i & 1) ? woB : woA) + (i >= WPA ? wo[(i + 16 - WPA) & 15][0] & dZ : 0) + (i >> 1) * 2048);
        xpre = xdesc(0);
        asm volatile("" : "+l"(xpre));
        uint64_t vpre = 0;
        if (VW) { vpre = mkdesc(__shfl_sync(~0u, 1024 + WVS + wg * NVS * 2048, 0), 16, 1024); asm volatile("" : "+l"(vpre)); }
        BAR_SYNC(B_S, 416);
        if (s < 62) {
          float acc[16];
          if (VW) {
            WG_FENCE();
            wgmma_rs_n32_z(acc, wV[0], xpre);
#pragma unroll
            for (int i = NVR + NH - 1; i > 0 && i > NVR + NH - VO; i--) wgmma_rs_n32(acc, i < NVR ? wV[i] : vS[i - NVR], xpre + (i >> 2) * 256 + (i & 3) * 2, 1);
#pragma unroll
            for (int i = NVR + NH; i < 16; i++) wgmma_ssT_n32(acc, vpre + (i - NVR) * 128, xpre + (i >> 2) * 256 + (i & 3) * 2, 1);
#pragma unroll
            for (int i = NVR + NH - VO; i > 0; i--) wgmma_rs_n32(acc, i < NVR ? wV[i] : vS[i - NVR], xpre + (i >> 2) * 256 + (i & 3) * 2, 1);
            WG_COMMIT();
          } else rs_issue(acc, wQ, s + 2, true, true);
          mbar_wait(sb + BARS + 24, (s + 1) & 1);
          WG_WAIT(0);
#pragma unroll
          for (int i = NW1; i < NWB; i++) ldsm4t(wo[i], ((i & 1) ? woB : woA) + (i >= NW1 + WPC ? wo[(i + 16 - WPC) & 15][0] & dZ : 0) + (i >> 1) * 2048);
          const uint32_t d = park_ptr();
          BAR_SYNC(B_V, 512);
          park(acc, 0, 2, d);
        } else {
#pragma unroll
          for (int i = NW1; i < NWB; i++) ldsm4t(wo[i], ((i & 1) ? woB : woA) + (i >> 1) * 2048);
          BAR_SYNC(B_V, 512);
        }
#pragma unroll
        for (int i = NWB; i < NWP; i++) ldsm4t(wo[i], ((i & 1) ? woB : woA) + (i >> 1) * 2048);
        float inv0, inv1;
        SCHED_FENCE(57);
        BAR_SYNC(B_O, 416);
        float c[2][4] = {{0, 0, 0, 0}, {0, 0, 0, 0}};
        uint32_t o[4][4], arD;
#pragma unroll
        for (int i = 0; i < 2; i++) ldsm4t(o[i], oA + i * 512);
        SCHED_FENCE(46);
#pragma unroll
        for (int i = 0; i < 16; i++) {
          mma16(c[i & 1], wo[i][0], wo[i][1], wo[i][2], wo[i][3], o[i >> 2][i & 2], o[i >> 2][(i & 2) + 1]);
          if (i == 1) ldsm4t(o[2], oA + 1024);
          if (i == 7) { ldsm4t(o[3], oA + 1536); arD = lds1(tp + T_AR); }
          if (i == 8) {
            const uint2 u = lds2u((oA & 0xff000030u) / 2 + (oA & 0xff000000u) / 2 + 1024 + BARS + 192);
            asm("rcp.approx.ftz.f32 %0,%1;" : "=f"(inv0) : "f"(F_(u.x)));
            asm("rcp.approx.ftz.f32 %0,%1;" : "=f"(inv1) : "f"(F_(u.y)));
          }
          if (i + NWP < 16) ldsm4t(wo[(i + NWP) & 15], (((i + NWP) & 1) ? woB : woA) + ((i + NWP) >> 1) * 2048);
        }
        stsm4(arD, pk(c[0][0] * inv0, c[0][1] * inv1), pk(c[0][2] * inv0, c[0][3] * inv1), pk(c[1][0] * inv0, c[1][1] * inv1), pk(c[1][2] * inv0, c[1][3] * inv1));
      }
      const uint32_t d = park_ptr();
      BAR_SYNC(B_W, 384);
      if (s < 62) {
        vk_pass(s + 2, d, false);
        BAR_ARRIVE(B_P, 384); BAR_ARRIVE(B_X, 320);
        TS(10);
      } else {
        mA = lds1(tp + T_MEM);
      }
    }
  } else if (role == 3) {
    asm volatile("setmaxnreg.dec.sync.aligned.u32 24;");
    if (blockIdx.x >= 128) {
      if (threadIdx.x < 416) {
#pragma unroll 1
        for (int k = 0; k < 32; k++) {
          BAR_SYNC(B_W, 288);
          asm volatile("{.reg .pred p; elect.sync _|p, 0xffffffff; @p cp.async.bulk.tensor.3d.global.shared::cta.bulk_group [%0,{0,%1,%2}],[%3]; cp.async.bulk.commit_group;}"
                       ::"l"(&mp.hst), "r"((blockIdx.x & 1) * 16), "r"(k * 32 + (blockIdx.x & 2) * 8), "r"(sb + 152 * 1024 + (k & 1) * 32768) : "memory");
          if (k < 4 || (k & 3) == 3)
            asm volatile("{.reg .pred p; cp.async.bulk.wait_group 0; elect.sync _|p, 0xffffffff; @p st." HREL ".gpu.global.u32 [%0],%1;}" ::"l"((unsigned*)&g_hprog + (blockIdx.x & 3)), "r"(k + 1) : "memory");
          else BULK_WAIT_READ(0);
        }
        BAR_ARRIVE(B_O, 320);
      } else if (threadIdx.x < 448) {
        wait_h(HPW);
#pragma unroll 1
        for (int r0 = 0; r0 < 1024; r0 += 128) {
          if (r0 == HPR) BAR_ARRIVE(B_O, 320);
          if (threadIdx.x == 416) {
#pragma unroll 1
            for (int r = r0; r < r0 + 128; r += 32) {
#pragma unroll 1
              for (int c = 0; c < 4; c++) {
                tma2d_pf(&mp.wm, 2048 + (blockIdx.x & 3) * 1024 + c * 256, r);
                wait_until(clk(), HPS);
              }
            }
          }
          __syncwarp();
        }
      }
      return;
    }
    ROLE_VARS
    const uint32_t L16 = sb + (tid & 31) * 16;
    CLUSTER_SYNC();
    sts1(sb + PACE + 36, LO(xc) + h * 262144 + X_VM(0));
    auto vm_stage = [&](int s) {
      const uint32_t tag = ((s >> 1) + 1) & 1;
      const char* xm = mkp(lds1(sb + PACE + 36) + (s & 1) * X_RING + iw * XC + (l16 >> 1), HI(xc));
      uint2 m[4];
      CONSUME(LO(xm));
      BAR_SYNC(B_S2, 256);
      if (dZ2 > 1) { const uint32_t c = clk(); while (clk() - c < (uint32_t)dZ2) {} }
      int it = 0;
      while (true) {
#pragma unroll
        for (int i = 0; i < 4; i++) m[i] = ldg_b64(xm + (i >> 1) * 2048 + (i & 1) * 256);
        sts4(L16 + VN + iw * 512, m[0].x, m[0].y, m[1].x, m[1].y);
        sts4(L16 + VN + iw * 512 + 2048, m[2].x, m[2].y, m[3].x, m[3].y);
        if (!anybad(m[0].x, m[1].x, m[2].x, m[3].x, tag)) break;
        RP(2);
        if (++it > SPIN_LIMIT) __trap();
      }
      if (s < 63) BAR_ARRIVE(B_V, 512); else BAR_ARRIVE(B_V, 256);
    };
    if (iw == 0) {
      wait_h(1);
#pragma unroll 1
      for (int s = 0; s < 63; s++) {
        if (s) BAR_SYNC(B_R, 320); else BAR_SYNC(B_Q, 288);
        if (s < 62)
          asm volatile("{.reg .pred p; elect.sync _|p, 0xffffffff; @p mbarrier.arrive.expect_tx.shared.b64 _,[%2],32768;\n"
                       "@p cp.async.bulk.shared::cluster.global.mbarrier::complete_tx::bytes.L2::cache_hint [%0],[%1],32768,[%2],%3;}"
                       ::"r"(sb + XB), "l"(g_h + (s + 2) * 4096 + a * 2048), "r"(sb + BARS + 136), "l"(pol_stream()) : "memory");
        if (s >= 7) {
          const uint32_t zo = b * 160 + l16;
          if (l16 < 160) CONSUME(exch_b128((char*)g_ar + (zo >> 7) * 1024 + (zo & 127) + ((s + 1) & 7) * 128, 0, 0, 0, 0).x);
          __syncwarp();
        }
        if (s < 62) mbar_wait(sb + BARS + 136, (s + X1) & 1);
        BAR_ARRIVE(B_S, 416);
        vm_stage(s);
        BAR_ARRIVE(B_O, 416);
        BAR_SYNC(B_W, 384);
        FENCE_ASYNC_SMEM();
        asm volatile("{.reg .pred p; elect.sync _|p, 0xffffffff; @p cp.reduce.async.bulk.tensor.2d.global.shared::cta.add.bulk_group [%0,{%1,%2}],[%3];}"
                     ::"l"(&mp.ari), "r"((s & 7) * 64), "r"(j * 40), "r"(sb + ARO) : "memory");
        BULK_COMMIT();
        asm volatile("st.relaxed.gpu.global.u32 [%0],%1;" ::"l"(g_tm + (s & 1) * 128 + b), "r"(gtime()) : "memory");
        TS(3);
        if ((s & 1) && s < 61) wait_h((s + 3) >> 1);
        else if (!(s & 3) && s && b < 2 * GT)
          asm volatile("{.reg .pred p; elect.sync _|p, 0xffffffff; @p red.release.gpu.global.add.u32 [%0],1;}" ::"l"(g_oc + (s - 4) * 8) : "memory");
        BULK_WAIT_READ(0);
      }
      BAR_ARRIVE(B_R, 320);
    } else if (iw == 1) {
      const uint32_t pc = sb + MEM + (lane >> 2) * 640 + (lane & 3) * 144 + (lane & 12), pd = sb + MEM + (lane & 15) * 640 + 576 + (lane & 3) * 16 + (lane & 12);
      uint32_t T = 0, par = 0;
      int est = dA;
      mbar_wait_q(sb + BARS + 88, 0);
      wait_until(clk(), LD3);
#pragma unroll 1
      for (int c = 0; c < 4; c++)
        asm volatile("{.reg .pred p; elect.sync _|p, 0xffffffff; @p cp.async.bulk.prefetch.L2.global [%0], 8192;}" ::"l"((const char*)x + b * 8192 + c * 1048576) : "memory");
#pragma unroll 1
      for (int s = 0; s < 63; s++) {
        if (s) {
          const uint4 tm = ldg_rlx4((const char*)g_tm + ((s + 1) & 1) * 512 + l16);
          const int t0 = tm.x - T, t1 = tm.y - T, t2 = tm.z - T, t3 = tm.w - T;
          const int e = max(dF + (__reduce_add_sync(~0u, (t0 + t1) + (t2 + t3)) >> 7), dV + __reduce_max_sync(~0u, max(max(t0, t1), max(t2, t3))));
          if (s > 1) est += max(min(e >> (e > 0 ? 2 : 1), dP), -dX2);
          T += (s == 1 || e > dM ? e : 0) + est;
        }
        vm_stage(s);
        BAR_SYNC(B_W, 384);
        SCHED_FENCE(70);
        const uint32_t tW = gtime();
        if (s == 0) T = tW + 800;
        const uint32_t te = tW + min(max((int)(T - tW), dD), 2000);
        while ((int)(gtime() - te) < 0) {}
        TS(7);
        int it = 0;
        while (true) {
          ar_fetch(sb + MEM, &mp.ari, s & 7, a, sb + BARS + 112);
          mbar_wait(sb + BARS + 112, par);
          par ^= 1;
          const uint32_t n0 = lds1(pc), n1 = lds1(pc + 5120), n2 = lds1(pd);
          if (!__any_sync(~0u, (tagbad(n0, n1, 0x42004200) | (n2 ^ 0x42004200)) != 0)) break;
          RP(0);
          if (++it > SPIN_LIMIT) __trap();
        }
        BAR_ARRIVE(B_R, 320);
        TS(11);
      }
    } else {
#define V_LOAD(n) asm volatile("{.reg .pred p; elect.sync _|p, 0xffffffff; @p mbarrier.arrive.expect_tx.shared.b64 _,[%3],8192;\n" \
        "@p cp.async.bulk.tensor.5d.shared::cluster.global.mbarrier::complete_tx::bytes [%0+%4],[%1,{0,0,0,0,%2}],[%3];\n" \
        "@p cp.async.bulk.tensor.5d.shared::cluster.global.mbarrier::complete_tx::bytes [%0+%5],[%1,{0,0,0,1,%2}],[%3];}" \
        ::"r"(sb), "l"(&mp.vx), "r"(h * 32 + X_VRING(n) / 8192), "r"(sb + BARS + 8), "n"(VX0), "n"(VX1) : "memory")
      uint32_t src = L16 + PK + (iw & 1) * 2048;
#define qd (L16 + (lane >> 4) * 256 + QT + (iw & 1) * 1024)
#define vd (LO(xc) + h * 262144 + j * XC + (iw & 1) * 2048 + l16)
#define FINISH [&](int n, int m) { \
_Pragma("unroll") \
        for (int i = 1; i >= 0; i--) { \
          const uint32_t p = src + m * 4096 + i * 512; \
          uint4 u; \
            asm volatile("{.reg .b32 a<4>, b<4>, c<4>, d<4>;\n" \
              "ld.shared.v4.u32 {a0,a1,a2,a3},[%4]; ld.shared.v4.u32 {b0,b1,b2,b3},[%4+1024]; ld.shared.v4.u32 {c0,c1,c2,c3},[%4+12288];\n" \
              "add.rn.bf16x2 a0,a0,b0; add.rn.bf16x2 a1,a1,b1; add.rn.bf16x2 a2,a2,b2; add.rn.bf16x2 a3,a3,b3;\n" \
              "lop3.b32 d0,a0,%5,%4,0xea; ld.shared.v4.u32 {b0,b1,b2,b3},[d0+13312];\n" \
              "add.rn.bf16x2 a0,a0,c0; add.rn.bf16x2 a1,a1,c1; add.rn.bf16x2 a2,a2,c2; add.rn.bf16x2 a3,a3,c3;\n" \
              "add.rn.bf16x2 %0,a0,b0; add.rn.bf16x2 %1,a1,b1; add.rn.bf16x2 %2,a2,b2; add.rn.bf16x2 %3,a3,b3;}" \
              : "=r"(u.x), "=r"(u.y), "=r"(u.z), "=r"(u.w) : "r"(p), "r"(dZ) : "memory"); \
          if (m == (VW ? 0 : 2)) stg_b128(mkp(vd ^ X_VRING(n), HI(xc)) + i * 512, (u.x & ~1u) | X_VTAG(n), u.y, u.z, u.w); \
          else stsm4(qd + (n & 1) * 4096 + (m & 1) * 2048 + i * 256, u.x, u.z, u.y, u.w); \
          SCHED_FENCE(71 + m * 2 + i); \
        } \
      }
#pragma unroll 1
      for (int n = 0; n < 64; n++) {
        src = PIN(src);
        b = __shfl_sync(~0u, lds1(sb + PACE + 24), 0);
        const uint32_t L16 = src - PK - (iw & 1) * 2048;
        auto finish = FINISH;
        if (n < 2) BAR_SYNC(B_C, 320);
        if (n == 1) BAR_ARRIVE(B_T0, 320);
        mbar_wait(sb + BARS + 16, n & 1);
        finish(n, 0);
        __syncwarp();
        if (lane == 0 && n < 63) mbar_arrive_cl(mapa(sb, a ^ 1) + BARS + 24);
        BAR_SYNC(B_K, 320);
        mbar_wait(sb + BARS + 40, n & 1);
        finish(n, 2);
        BAR_SYNC(B_X, 320);
        mbar_wait(sb + BARS + 32, n & 1);
        finish(n, 1);
        BAR_SYNC(B_T, 64);
        if (lane == 0 && n < 63) {
          if (iw == 2) { mbar_expect(sb + BARS + 16, 4096); mbar_expect(sb + BARS + 32, 4096); mbar_expect(sb + BARS + 40, 4096); }
          mbar_arrive_cl(mapa(sb, a ^ 1) + BARS + 80);
        }
        __syncwarp();
        if (n) {
          vm_stage(n - 1);
          BAR_SYNC(B_W, 384);
        } else {
          if (X1) BAR_SYNC(B_H, 320); else BAR_SYNC(B_C, 320);
        }
        if (iw == 2) { wait_until(clk(), VDL); V_LOAD(n); }
      }
#undef qd
#undef vd
    }
    vm_stage(63);
  } else {
    asm volatile("setmaxnreg.dec.sync.aligned.u32 %0;" ::"n"(RA_));
    if (blockIdx.x >= 128) return;
    ROLE_VARS
    uint32_t L16 = __shfl_sync(~0u, sb + (tid & 31) * 16, tid & 31);
    CLUSTER_ARRIVE();
    if (tid == 256) {
      const int col = h * 128 + bb * 64;
      for (int c = 0; c < 12 + WIN; c++) {
        const uint32_t mb = sb + PACE + (c % WIN) * 8;
        if (c >= WIN) mbar_wait(mb, (c / WIN - 1) & 1);
        if (c == 7 + WIN) asm volatile("mbarrier.arrive.shared.b64 _,[%0];" ::"r"(wbar) : "memory");
        if (c >= 12) continue;
        if (c == 1) wait_until(clk(), LD1);
        mbar_expect(mb, 16384);
        if (c < 8) tma2d_s(sb + (c & 1) * XB + (c >> 1) * 16384, (c & 1) ? &mp.wk : &mp.wq, col, a * 512 + (c >> 1) * 128, mb);
        else
#pragma unroll 1
          for (int i = (c & 1) * 8; i < (c & 1) * 8 + 8; i++) {
            const int w = (c - 8) >> 1;
            tma2d_s(i < NVR ? sb + MEM + (w * NVR + i) * 2048 : sb + WVS + (w * NVS + i - NVR) * 2048, &mp.wv, col, a * 512 + w * 256 + i * 16, mb);
          }
      }
      asm volatile("mbarrier.arrive.shared.b64 _,[%0];" ::"r"(sb + BARS + 88) : "memory");
      PTT(61, 256);
      wait_until(clk(), LD2);
#pragma unroll 1
      for (int c = 0; c < 4; c++) tma2d_pf(&mp.wo, j * 256 + c * 64, h * 128);
    }
    __syncwarp();
    CLUSTER_WAIT();
#define pr (L16 + SC)
    {
      const int lim = j * 8 + iw * 2 - (lane & 7) - (lane & 8) * 2;
      const bool mk = L16 & 256;
      const int rw = lane >> 2;
      sts4(L16 + TA + iw * 512,
           iw != 2 ? L16 + KT + (iw & 1) * 256 + (lane >> 4) * 256 : sb + RK + (L16 & 0x80) * 2 + ((L16 >> 1) & 0x80) + (L16 & 0x70),
           L16 + QT + (lane >> 3) * 384, sb + SC + min(lane >> 3, 2) * 256 + (L16 & 0x70) + iw * 4, L16 + (lane >> 4) * 256 + QT + (iw >> 1) * 1024 + (iw & 1) * 256);
      const uint4 u = make_uint4(mk ? 0u : (lim < 0 ? 0xfc00u : 0u) | (lim < -1 ? 0xfc000000u : 0u),
           mk ? 0xfc00fc00u : (lim < 8 ? 0xfc00u : 0u) | (lim < 7 ? 0xfc000000u : 0u),
           ((h * 2 + (iw >> 1)) * 1024 + (j * 8 + rw) * 8 + (((iw & 1) * 4 + ((lane & 3) ^ (rw >> 1))) ^ rw)) * 16, sb + OT + iw * 512 + (L16 & 0x70) * 4 + (((L16 >> 3) ^ (L16 >> 1)) & 0x30));
      if (AT8) { const uint32_t t = sb + TA + 2048 + iw * 512 + lane * 8; sts1(t, u.x); sts1(t + 4, u.y); sts1(t + 256, u.z); sts1(t + 260, u.w); }
      else sts4(L16 + TA + 2048 + iw * 512, u.x, u.y, u.z, u.w);
    }
    {
      const uint32_t xh = LO(xc) + h * 262144, xs = xh + X_SC + iw * 1024 + min(lane, 16 + (lane & 7)) * 8;
      sts4(L16 + TA + 4096 + iw * 512, xh + X_SC + j * 256 + iw * 64 + lpub, xs, dS, iw != 2 ? 0 : U_(SCS));
      sts1(L16 + TA + 12 + iw * 512, xs + X_TOK + j * 4096);
      if (AT8) { const uint32_t t = sb + TA + 6144 + iw * 256 + lane * 8; sts1(t, xs + X_TOK + j * 4096); sts1(t + 4, lds1(L16 + TA + 8 + iw * 512)); }
    }
    uint32_t tA = L16 + TA + iw * 512;
#define tw (tA - L16 != TA + 1024)
#define w3_ (tA - L16 == TA + 1536)
#define XP_(lo) mkp(lo, HI(xc))
    auto publish = [&](char* d, const uint2& w) { stg_b64(d, w.x, w.y); };
    {
      const uint32_t xo = lds1(tA + 4096);
#pragma unroll 1
      for (int i = 0; i < 10; i++) stg_b64(XP_(xo + (i & 1) * X_RING + (i >> 1) * 4096), 0, 0);
    }
    BAR_SYNC(B_P, 384);
    for (int s = 0; s < 64; s++) {
      asm volatile("" : "+r"(L16), "+r"(tA));
      const uint32_t tag = ((s >> 1) + 1) & 1, ring = (s & 1) * X_RING;
      const uint4 t0 = lds4(tA);
      const uint4 tx = lds4(tA + 4096);
      const uint32_t xo = tx.x ^ ring, xs = tx.y ^ ring;
      const float gm = F_(tx.w);
      const uint32_t qA = t0.y + (ring >> 5);
      uint32_t c0;
      uint2 ts[4];
      uint4 v[4];
      uint32_t af[2][4], qt[4][4];
      {
        const uint32_t aA = t0.x + (tw ? ring >> 5 : 0);
        uint32_t ql[2][4], qr[2][4];
        uint2 pw_;
        float c[4] = {0, 0, 0, 0}, d[4] = {0, 0, 0, 0};
        if (s == PDS) asm volatile("griddepcontrol.launch_dependents;");
#pragma unroll
        for (int i = 0; i < 4; i++) ldsm4t(qt[i], qA + i * 128);
        mbar_wait(sb + BARS + 8, s & 1);
        TS(4);
        BAR_SYNC(B_E, 256);
#define PACK(c) make_uint2(pkh(fmaf(c[2], gm, c[0] * SCS), fmaf(c[3], gm, c[1] * SCS), tag), pkh(c[2] * SCS, c[3] * SCS, tag))
        ldsm4t(ql[0], L16 + RQ); ldsm4t(ql[1], L16 + RQ + 1024); ldsm4t(af[0], aA); ldsm4t(af[1], aA + 1024);
        CONSUME(xo);
#define QSUM(t, i) addbf(addbf(ql[t][i], ql[t][i + 2]), addbf(qr[t][i], qr[t][i + 2]))
#define STAIL mma16(c, af[0][0], af[0][1], af[0][2], af[0][3], QSUM(0, 0), QSUM(0, 1)); mma16(d, af[1][0], af[1][1], af[1][2], af[1][3], QSUM(1, 0), QSUM(1, 1));
        if (tw) {
          mbar_wait(sb + BARS, s & 1);
          TS(8);
          ldsm4t(qr[0], L16 + RQ + 512); ldsm4t(qr[1], L16 + RQ + 1536);
          STAIL
          pw_ = make_uint2(pkh(c[0] + d[0], c[1] + d[1], tag), pkh(c[2] + d[2], c[3] + d[3], tag));
        } else {
          uint32_t ar[2][4];
          mbar_wait(sb + BARS, s & 1);
          ldsm4t(qr[0], L16 + RQ + 512); ldsm4t(qr[1], L16 + RQ + 1536); ldsm4t(ar[0], aA + 512); ldsm4t(ar[1], aA + 1536);
#pragma unroll
          for (int i = 0; i < 8; i++) af[i >> 2][i & 3] = addbf(af[i >> 2][i & 3], ar[i >> 2][i & 3]);
          STAIL
          pw_.x = pw_.y = pkh((c[0] + c[2]) + (d[0] + d[2]), (c[1] + c[3]) + (d[1] + d[3]), tag);
        }
        publish(XP_(xo), pw_);
        c0 = clk() + tx.z;
        TS(1);
      }
      uint2 r[4];
      {
        float e[4][4];
#pragma unroll
        for (int i = 0; i < 4; i++) e[i][0] = e[i][1] = e[i][2] = e[i][3] = 0.f;
        {
#pragma unroll
          for (int i = 0; i < 4; i++) mma16(e[i], af[0][0], af[0][1], af[0][2], af[0][3], qt[i][0], qt[i][1]);
#pragma unroll
          for (int i = 0; i < 4; i++) mma16(e[i], af[1][0], af[1][1], af[1][2], af[1][3], qt[i][2], qt[i][3]);
        }
        SCHED_FENCE(55);
        if (VE) {
          v[0] = lds4(tA + (VX0 - TA)); v[1] = lds4(tA + (VX0 - TA) + 2048); v[2] = lds4(tA + (VX1 - TA)); v[3] = lds4(tA + (VX1 - TA) + 2048);
          if (VE == 2) CONSUME(v[0].x & v[1].x & v[2].x & v[3].x);
        }
        if (s < 63) BAR_ARRIVE(B_S, 416);
        SCHED_FENCE(58);
        if (!VE) { v[0] = lds4(tA + (VX0 - TA)); v[1] = lds4(tA + (VX0 - TA) + 2048); v[2] = lds4(tA + (VX1 - TA)); v[3] = lds4(tA + (VX1 - TA) + 2048); }
#pragma unroll
        for (int i = 0; i < 4; i++) ts[i] = PACK(e[i]);
        while ((int)(clk() - c0) < 0) {}
        TS(5);
#pragma unroll
        for (int u = 0; u < 4; u++) r[u] = ldg_b64(XP_(xs) + u * 256);
        BAR_ARRIVE(B_S2, 256);
      }
      const uint32_t fn = (L16 & 256) ? 0xfc00fc00u : 0u;
      float4 e = softmax2<false>(r, 0, fn);
      const bool vbad = anybad(v[0].x, v[1].x, v[2].x, v[3].x, X_VTAG(s));
      if (BADS(r)) {
        int it = 0;
        if (s > 8) sts1(tA + 4096 + 8, min(lds1(tA + 4096 + 8) + dX, 500));
        do {
          RP(1);
          if (++it > SPIN_LIMIT) __trap();
#pragma unroll
          for (int u = 0; u < 4; u++) r[u] = ldg_b64(XP_(xs) + u * 256);
        } while (BADS(r));
        e = softmax2<false>(r, 0, fn);
      }
      sts1(t0.z, pk(e.x, e.y)); sts1(t0.z + 128, pk(e.z, e.w));
#pragma unroll
      for (int i = 0; i < 4; i++) publish(XP_(xo) + X_TOK + i * 4096, ts[i]);
      TS(6);
      if (s < 63) BAR_SYNC(B_V, 512); else BAR_SYNC(B_V, 256);
      uint32_t O[4];
      uint4 vn[2];
      {
        uint32_t p[4], pm;
        ldsm4t(p, pr);
        vn[0] = lds4(tA + (VN - TA)); vn[1] = lds4(tA + (VN - TA) + 2048);
        asm volatile("ldmatrix.sync.aligned.m8n8.x1.trans.shared.b16 {%0},[%1];" : "=r"(pm) : "r"(pr + 512) : "memory");
        pv_mem(p, pm, v, vn, O, sb + BARS + 192 + ((L16 >> 1) & 24), L16);
        if (vbad) {
          int it = 0;
          do {
            if (++it > SPIN_LIMIT) __trap();
#pragma unroll
            for (int u = 0; u < 4; u++) v[u] = ldg_b128(XP_((LO(xc) + (lds1(sb + PACE + 24) >> 2) * 262144 + ((tA - L16 - TA) >> 9) * XC + l16) ^ X_VRING(s)) + X_VX(u));
          } while (anybad(v[0].x, v[1].x, v[2].x, v[3].x, X_VTAG(s)));
          pv_mem(p, pm, v, vn, O, sb + BARS + 192 + ((L16 >> 1) & 24), L16);
        }
      }
      stsm4(tA + (OB - TA), O[0], O[1], O[2], O[3]);
      if (s < 63) BAR_ARRIVE(B_O, 416);
      TS(2);
      c0 = clk() + (LG && s == 63 ? 0 : dG);
      SCHED_FENCE(60);
      if (tA == sb + TA) mbar_expect(sb + BARS, 2048);
      const uint32_t vs[4] = {addbf(vn[0].x, vn[0].z), addbf(vn[0].y, vn[0].w), addbf(vn[1].x, vn[1].z), addbf(vn[1].y, vn[1].w)};
      {
        const uint2 t3 = AT8 ? lds2u(sb + TA + 6144 + ((tA - sb - TA) >> 1)) : make_uint2(lds1(tA + 12), lds1(tA + 8));
        const char* xt = XP_(t3.x ^ ring);
        const uint2 t1 = lds2u(AT8 ? tA - (l16 >> 1) + 2048 : tA + 2048);
        const uint32_t pw = t3.y;
        uint2 rt[4];
        CONSUME(LO(xt) ^ t1.x ^ pw);
        while ((int)(clk() - c0) < 0) {}
        int it = 0;
        do {
          if (++it > SPIN_LIMIT) __trap();
#pragma unroll
          for (int u = 0; u < 4; u++) rt[u] = ldg_b64(xt + u * 256);
        } while (BADS(rt));
        const float4 et = softmax2<true>(rt, t1.x, t1.y);
        sts1(pw + SCT, pk(et.x, et.y)); sts1(pw + SCT + 128, pk(et.z, et.w));
      }
      s = PIN(s);
      BAR_SYNC(B_SC, 128);
      {
        uint32_t Ot[4], p[4], pm;
        const uint2 t2 = lds2u(AT8 ? tA - (l16 >> 1) + 2048 + 256 : tA + 2048 + 8);
        ldsm4t(p, pr + SCT);
        asm volatile("ldmatrix.sync.aligned.m8n8.x1.trans.shared.b16 {%0},[%1];" : "=r"(pm) : "r"(pr + SCT + 512) : "memory");
        char* od = (char*)g_O + ((s >> 2) * 1048576 + (s & 3) * 4096) + t2.x;
        CONSUME(LO(od) ^ HI(od) ^ pm ^ p[3]);
        TS(9);
        if (s < 62) BAR_SYNC(B_P, 384);
        pv_tok(p, pm, v, vs, Ot);
        asm volatile("stmatrix.sync.aligned.m8n8.x4.trans.shared.b16 [%0],{%1,%2,%3,%4};" ::"r"(t2.y), "r"(Ot[0]), "r"(Ot[1]), "r"(Ot[2]), "r"(Ot[3]) : "memory");
        __syncwarp();
        *(uint4*)od = lds4(tA + (OT - TA));
      }
    }
  }
  PH(5);
  if (threadIdx.x == 0) FT(40);
  PDUMP();
}
#undef wg
#undef iw
#undef h
#undef j
#undef a
#undef bb
#undef oi
#undef owner
#undef pr
#undef PIN
#undef XP_
#undef tw
#undef w3_
#undef lane
#undef l16
#undef lrow
#undef lpub

namespace ffn {
constexpr uint32_t STG = 196608;
constexpr uint32_t PRM = 229376;
constexpr uint32_t BARS = PRM + 2176;
constexpr uint32_t SMEM = BARS + 16 * 8;
}
#define UBASE (g_O + rb * 65536)
struct FfnMaps { CUtensorMap wo, w1a, w1b, w2, xp, out, x, xps, wo4; int zero[16]; };

template <int N>
__device__ __forceinline__ void wg_ss(float* d, uint64_t a, uint64_t b, int sd) {
  if (N == 128) wgmma_ss_n128(d, a, b, sd);
  if (N == 192) wgmma_ss_n192(d, a, b, sd);
  if (N == 256) wgmma_ss_n256(d, a, b, sd);
}
template <int N>
__device__ __forceinline__ void ffn_issue(float* acc, uint32_t full, uint32_t par, uint32_t a, uint32_t b, bool first) {
  mbar_wait(full, par);
  const uint64_t da = mkdesc(0, 0, 1024) | a, db = mkdesc(0, 0, 1024) | b;
  WG_FENCE();
#pragma unroll
  for (int j = 0; j < 4; j++) wg_ss<N>(acc, da + j * 2, db + j * 128, !first || j);
  WG_COMMIT();
}
__device__ __forceinline__ void ffn_release(uint32_t leader, uint32_t e) {
  asm volatile("{.reg .pred p; setp.ne.u32 p,%0,0; @p mbarrier.arrive.shared.b64 _,[%1];}" ::"r"(leader), "r"(e) : "memory");
}
__device__ __forceinline__ void ffn_done(unsigned* cnt) {
  asm volatile("{.reg .pred p; cp.async.bulk.wait_group 0; elect.sync _|p, 0xffffffff; @p red.relaxed.gpu.global.add.u32 [%0],1;}" ::"l"(cnt) : "memory");
}
template <int N>
__device__ __forceinline__ void acc_fence(float* d) {
#pragma unroll
  for (int i = 0; i < N; i++) asm volatile("" : "+f"(d[i])::"memory");
}
__device__ __forceinline__ float gelu_h(float hx) {
  float t;
  asm("tanh.approx.f32 %0,%1;" : "=f"(t) : "f"(hx * fmaf(hx * hx, 8 * 0.0356774081f, 2 * 0.7978845608f)));
  return fmaf(hx, t, hx);
}
template <int N>
__device__ __forceinline__ void ffn_gelu(uint32_t (&u)[N], int i, const uint2& b, uint32_t stw, uint32_t z) {
  uint32_t o[4];
#pragma unroll
  for (int e = 0; e < 4; e++) {
    uint32_t h;
    asm("fma.rn.bf16x2 %0,%1,%2,%3;" : "=r"(h) : "r"(u[i * 4 + e]), "r"(0x3f003f00), "r"(e < 2 ? b.x : b.y));
    o[e] = pk(gelu_h(blo(h)), gelu_h(bhi(h)));
#pragma unroll
    for (int j = i * 4 + e; j < N - 16; j += 16) u[j] = u[j + 16] ^ z;
  }
  stsm4(stw ^ (i * 32), o[0], o[1], o[2], o[3]);
}
__device__ __forceinline__ void ffn_store(uint32_t stg, const uint4* dst) {
  FENCE_ASYNC_SMEM();
  __syncwarp();
  asm volatile("{.reg .pred p; elect.sync _|p, 0xffffffff; @p cp.async.bulk.global.shared::cta.bulk_group [%0],[%1],2048; cp.async.bulk.commit_group;\n"
               "cp.async.bulk.wait_group.read 1;}" ::"l"(dst), "r"(stg) : "memory");
  __syncwarp();
}
__device__ __forceinline__ uint32_t halfbf(uint32_t v) { return pk(0.5f * blo(v), 0.5f * bhi(v)); }

__device__ __forceinline__ void ffn_spare(const FfnMaps& mp, uint32_t sb, int cb, const char* x) {
  using namespace ffn;
  const int tid = threadIdx.x, lane = tid & 31, wid = __shfl_sync(~0u, tid >> 5, 0);
  const uint32_t full = sb + BARS, emp = full + 48, xbar = full + 104, XA = 147456;
  if (tid < 128) sts1(sb + PRM + (tid >> 4) * 64 + (tid & 3) * 16 + ((tid >> 2) & 3) * 4, pk(__ldcg(g_mod + 2048 + cb * 256 + tid * 2), __ldcg(g_mod + 2048 + cb * 256 + tid * 2 + 1)));
  __syncthreads();
  if (wid == 8) {
    int st = 0; uint32_t ph = 1;
#pragma unroll 1
    for (int rb = 0; rb < 16; rb++) {
#pragma unroll 1
      for (int i = rb ? 16 : 0; i < (rb < 15 ? 32 : 16); i++)
        asm volatile("prefetch.global.L2 [%0];" ::"l"(x + (rb * 128 + i * 8 + (lane >> 2)) * 2048 + cb * 512 + (lane & 3) * 128) : "memory");
      if (rb < 15) {
        int it = 0;
        while (ld_acq(g_oc + rb * 32) < 2 * GT) { __nanosleep(500); if (++it > SPIN_LIMIT) __trap(); }
      } else asm volatile("griddepcontrol.wait;" ::: "memory");
      FENCE_ASYNC_G();
#pragma unroll 1
      for (int k = 0; k < GT; k++) {
        mbar_wait_q(emp + st * 8, ph);
        e_expect_tma3d(sb + st * 49152 + 16384, &mp.wo4, k * 64, cb * 4, full + st * 8, 49152);
        e_bulk_ld(sb + st * 49152, g_O + rb * 65536 + k * 1024, 16384, full + st * 8);
        if (++st == 3) { st = 0; ph ^= 1; }
      }
    }
  } else if (wid < 8) {
    const int wg = wid >> 2, row0 = wid * 16;
    const uint32_t stg = sb + row0 * 128, stw = stg + (lane & 15) * 128 + (((lane >> 4) ^ (lane & 7)) << 4), prm = sb + PRM + (lane & 3) * 16;
    const uint32_t aw = (uint32_t)mkdesc(1024 + wg * 8192, 16, 0), leader = (tid & 127) == 0;
    constexpr uint32_t bw = (1024 + 16384) / 16 + (8192 / 16 << 16);
    int st = 0, prev = 0; uint32_t ph = 0;
#pragma unroll 1
    for (int rb = 0; rb < 16; rb++) {
      float acc[128];
      if (tid == 0) FT(44 + rb);
#pragma unroll 1
      for (int k = 0; k < GT; k++) {
        ffn_issue<256>(acc, full + st * 8, ph, aw + st * 3072, bw + st * 3072, k == 0);
        if (k == 2) {
          if (rb) ffn_done(g_oc + 480 + rb * 32 + cb);
          BAR_SYNC(1, 256);
          if (tid == 0) {
            mbar_expect(xbar, 65536);
            for (int i = 0; i < 4; i++) tma2d(sb + (i & 2 ? STG : XA) + (i & 1) * 16384, &mp.x, cb * 256 + i * 64, rb * 128, xbar);
          }
          __syncwarp();
        }
        WG_WAIT(1);
        ffn_release(leader && k, emp + prev * 8);
        prev = st;
        if (++st == 3) { st = 0; ph ^= 1; }
      }
      WG_WAIT(0);
      ffn_release(leader, emp + prev * 8);
      acc_fence<128>(acc);
      mbar_wait(xbar, rb & 1);
      uint4 pa, pn = lds4(prm);
      uint32_t xn[2][4];
#define XAD(j) ((stw ^ (((j) & 3) * 32)) + ((j) & 8 ? STG : XA) + ((j) & 4) * 4096)
      ldsm4(xn[0], XAD(0)); ldsm4(xn[1], XAD(1));
#pragma unroll
      for (int j = 0; j < 16; j++) {
        const uint32_t a = XAD(j), xv[4] = {xn[j & 1][0], xn[j & 1][1], xn[j & 1][2], xn[j & 1][3]};
        uint32_t o[4];
        if (j < 14) ldsm4(xn[j & 1], XAD(j + 2));
        if (!(j & 1)) { pa = pn; if (j < 14) pn = lds4(prm + ((j >> 1) + 1) * 64); }
#pragma unroll
        for (int e = 0; e < 4; e++) {
          const uint32_t g = (j & 1) ? (e < 2 ? pa.z : pa.w) : (e < 2 ? pa.x : pa.y);
          o[e] = pk(fmaf(blo(g), acc[j * 8 + e * 2], blo(xv[e])), fmaf(bhi(g), acc[j * 8 + e * 2 + 1], bhi(xv[e])));
        }
        stsm4(a, o[0], o[1], o[2], o[3]);
      }
      FENCE_ASYNC_SMEM();
      __syncwarp();
#pragma unroll 1
      for (int i = 0; i < 4; i++)
        asm volatile("{.reg .pred p; elect.sync _|p, 0xffffffff; @p cp.async.bulk.tensor.2d.global.shared::cta.bulk_group [%0,{%1,%2}],[%3];}"
                     ::"l"(&mp.xps), "r"(cb * 256 + i * 64), "r"(rb * 128 + row0), "r"(stg + (i & 2 ? STG : XA) + (i & 1) * 16384) : "memory");
      BULK_COMMIT();
    }
    ffn_done(g_oc + 512 + 15 * 32 + cb);
  }
  __syncthreads();
}

#define SL(st) (GT % 6 == 0 ? (st) : (st) + GT % 6 - ((st) >= 6 - GT % 6 ? 6 : 0))
__global__ void __launch_bounds__(384, 1)
k_ffn(const __grid_constant__ FfnMaps mp, const bf16* __restrict__ b1, const bf16* __restrict__ b2, const char* x) {
  using namespace ffn;
  extern __shared__ __align__(1024) char smem[];
  const uint32_t sb = (uint32_t)__cvta_generic_to_shared(smem);
  if ((sb & 0x3FFFF) != 1024) __trap();
  const int tid = threadIdx.x, lane = tid & 31, wg = __shfl_sync(~0u, tid >> 7, 0);
  int tile = ((int)blockIdx.x + 128) % 132;
  uint4 hs = ldg_rlx4(g_hsm);
  if (TMP && tid == 256) asm volatile("prefetch.tensormap [%0];" ::"l"(&mp.wo) : "memory");
  const uint32_t full = sb + BARS, emp = full + 48, xbar = full + 96, rdy = full + 96;
  if (tid == 256) {
#pragma unroll
    for (int i = 0; i < 6; i++) mbar_init(full + i * 8, 1);
    FENCE_ASYNC_SMEM();
  } else if (tid == 288) {
#pragma unroll
    for (int i = 0; i < 6; i++) mbar_init(emp + i * 8, 2);
  } else if (tid == 320) {
    mbar_init(xbar, 2);
#pragma unroll
    for (int i = 1; i < 4; i++) mbar_init(rdy + i * 8, 1);
    FENCE_ASYNC_SMEM();
  }
  __syncthreads();
  {
    uint32_t sm, nsm;
    asm volatile("mov.u32 %0,%%smid; mov.u32 %1,%%nsmid;" : "=r"(sm), "=r"(nsm));
    const uint32_t t = sm >> 1, u = ((t - 32) * 37) >> 8;
    const uint32_t g = t < 32 ? t & 7 : t < 60 ? t - 31 - u * 7 : 0, i = (t < 32 ? t >> 3 : t < 60 ? 4 + u : t - 58) * 2 + (sm & 1);
    const uint32_t m = ((g >> 1) * 4 + (i & 3)) * 8 + (g & 1) * 4 + (i >> 2);
    const bool usual = ((hs.x & hs.y & hs.z & hs.w) >> 2) == 30 && ((hs.x | hs.y | hs.z | hs.w) >> 2) == 30;
    if (nsm == 132)
      tile = sm == hs.x ? 128 : sm == hs.y ? 129 : sm == hs.z ? 130 : sm == hs.w ? 131 : usual ? m : sm - (hs.x < sm) - (hs.y < sm) - (hs.z < sm) - (hs.w < sm);
    tile = __shfl_sync(~0u, tile, 0);
  }
  if (tile >= 128) {
    ffn_spare(mp, sb, tile & 3, x);
    if (tid == 0) wait_cnt(&g_fcnt, 128);
    return;
  }
  const int rb = tile >> 3, nb = tile & 7;
  if (tid == 256) FT(34);
  const int wid = __shfl_sync(~0u, tid >> 5, 0);
  if (wid == 8) {
#pragma unroll
    for (int k = 0; k < 6; k++) { if (k) wait_until(clk(), 200); e_expect_tma3d<true>(sb + SL(k) * 32768 + 16384, &mp.wo, (GT + k) * 64, nb * 2, full + k * 8, 32768); }
    if (lane == 0) FT(36);
  } else if (wid == 9) {
    asm volatile("griddepcontrol.wait;" ::: "memory");
    if (lane == 0) FT(35);
    FENCE_ASYNC_G();
#pragma unroll
    for (int k = 0; k < 6; k++) { if (k) wait_until(clk(), 200); e_bulk_ld<true>(sb + SL(k) * 32768, g_O + rb * 65536 + (GT + k) * 1024, 16384, full + k * 8); }
    if (lane == 0) FT(2);
  } else if (tid == 320) {
    asm volatile("red.relaxed.gpu.global.add.u32 [%0],1;" ::"l"(&g_fcnt) : "memory");
  }
  unsigned* cnt = g_cnt + rb * 128;
  if (wg == 2) {
    asm volatile("setmaxnreg.dec.sync.aligned.u32 40;");
    const int pw = __shfl_sync(~0u, (tid >> 5) & 3, 0);
    uint32_t me = emp, mp_ = 0, st = 0;
    auto wait1 = [&]() { mbar_wait_q(me, mp_); me += 8; if (me == emp + 48) { me = emp; mp_ ^= 1; } };
#define NEXTS() do { if (++st == 6) st = 0; } while (0)
#define KT2(k) ((k) < 2 ? nb * 2 + (k) : (k) >= 16 ? (k) - 16 : (k) - 2 < nb * 2 ? (k) - 2 : (k))
#define KT3(k) (((k) & 7) * 7 + ((k) >> 3))
    if (pw == 0) {
#pragma unroll 1
      for (int k = GT + 6; k < 64; k++) {
        wait1();
        e_expect_tma3d<true>(sb + SL(st) * 32768 + 16384, &mp.wo, k * 64, nb * 2, full + st * 8, 32768);
        NEXTS();
      }
      wait1(); wait1(); wait1();
#pragma unroll 1
      for (int k = 0; k < 32; k++) {
        const int kt = KT2(k);
        if (k != 3) wait1();
        e_expect_tma3d<true>(sb + (k & 3) * 49152 + 16384, k < 16 ? &mp.w1a : &mp.w1b, kt * 64, nb * 7 + (k >> 4) * 4, full + st * 8, k < 2 ? 32768 : k < 16 ? 49152 : 40960);
        NEXTS();
      }
#pragma unroll 1
      for (int k = 0; k < 56; k++) {
        if (k != 2 && k != 5) wait1();
        e_expect_tma3d<true>(sb + SL(st) * 32768 + 16384, &mp.w2, KT3(k) * 64, nb * 2, full + st * 8, 32768);
        NEXTS();
      }
    } else if (pw == 1) {
      const uint4* A = g_O + rb * 65536;
#pragma unroll 1
      for (int k = GT + 6; k < 64; k++) {
        wait1();
        e_bulk_ld<true>(sb + SL(st) * 32768, A + k * 1024, 16384, full + st * 8);
        NEXTS();
      }
#pragma unroll 1
      for (int k = 0; k < 6; k++) wait1();
      wait_cnt(cnt, 64);
      if (lane == 0) FT(29);
      FENCE_ASYNC_G();
      st = (66 - GT) % 6;
      A = g_h2 + rb * 16384;
#pragma unroll 1
      for (int k = 2; k < 32; k++) {
        const int kt = KT2(k);
        if (k > 3) wait1();
        if (k == 3) wait_until(clk(), 250);
        e_bulk_ld(sb + (k & 3) * 49152, A + kt * 1024, 16384, full + st * 8);
        NEXTS();
      }
      A = UBASE;
#pragma unroll 1
      for (int k = 0; k < 56; k++) {
        if ((k & 15) == 0 && k < 48) { mbar_wait_q(rdy + 8 + (k >> 1), 0); FENCE_ASYNC_G(); }
        if (k != 2 && k != 5) wait1();
        e_bulk_ld<true>(sb + SL(st) * 32768, A + KT3(k) * 1024, 16384, full + st * 8);
        NEXTS();
      }
    } else if (pw == 2) {
      asm volatile("griddepcontrol.wait;" ::: "memory");
      if (lane < 16) g_modp[tile * 16 + lane] = make_uint4(0, 0, 0, 0);
      if (lane == 16 && tile == 0) g_hprog = make_uint4(0, 0, 0, 0);
      __nanosleep(2000);
      if (lane < 5) asm volatile("prefetch.tensormap [%0];" ::"l"(&mp.w1a + lane) : "memory");
      int it = 0;
      while (ld_acq(g_oc + 512 + rb * 32 + (nb >> 1)) < 8) { __nanosleep(200); if (++it > SPIN_LIMIT) __trap(); }
      FENCE_ASYNC_G();
#pragma unroll
      for (int i = 0; i < 8; i++) asm volatile("prefetch.global.L2 [%0];" ::"l"((const char*)g_xp + (rb * 128 + i * 16 + (lane >> 1)) * 2048 + nb * 256 + (lane & 1) * 128) : "memory");
      if (!it) __nanosleep(1500);
      if (lane == 0) {
        mbar_expect(xbar, 32768);
        tma2d(sb + STG, &mp.xp, nb * 128, rb * 128, xbar);
        tma2d(sb + STG + 16384, &mp.xp, nb * 128 + 64, rb * 128, xbar);
      }
    } else {
      const uint32_t prm = sb + PRM;
      const uint2 v2 = ((const uint2*)(b2 + nb * 128))[lane];
      auto put = [&](uint32_t at, uint32_t u, uint32_t v) {
        const uint32_t a = prm + at + (lane >> 3) * 64 + (lane & 1) * 32 + ((lane >> 1) & 3) * 4;
        sts1(a, u); sts1(a + 16, v);
      };
      put(1024, v2.x, v2.y);
#pragma unroll
      for (int i = 0; i < 7; i++) sts1(prm + 1280 + i * 128 + (lane & 3) * 32 + (lane >> 2) * 4, halfbf(((const uint32_t*)(b1 + nb * 448))[i * 32 + lane]));
      const float4* md = (const float4*)(g_mod + nb * 128) + lane;
      const float4 ga = __ldcg(md + 512), sbv = __ldcg(md + 768), cb = __ldcg(md + 1024), gb = __ldcg(md + 1280);
      put(0, pk(ga.x, ga.y), pk(ga.z, ga.w));
      put(256, pk(1.f + cb.x, 1.f + cb.y), pk(1.f + cb.z, 1.f + cb.w));
      put(512, pk(sbv.x, sbv.y), pk(sbv.z, sbv.w));
      put(768, pk(gb.x, gb.y), pk(gb.z, gb.w));
      __syncwarp();
      if (lane == 0) {
        asm volatile("mbarrier.arrive.shared.b64 _,[%0];" ::"r"(xbar) : "memory");
#pragma unroll 1
        for (int i = 1; i < 4; i++) {
          int it = 0;
          while (ld_acq(cnt + i * 32) < 64) { __nanosleep(200); if (++it > SPIN_LIMIT) __trap(); }
          asm volatile("mbarrier.arrive.shared.b64 _,[%0];" ::"r"(rdy + i * 8) : "memory");
        }
      }
    }
  } else {
    const int w = __shfl_sync(~0u, (tid >> 5) & 3, 0), q = lane & 3;
    const uint32_t leader = (tid & 127) == 0;
    const uint32_t prm = sb + PRM + q * 16;
#define PRM2(v, a, b, at) if (!(j & 1)) v = lds4(prm + (at) + (j >> 1) * 64); const uint32_t a = (j & 1) ? v.z : v.x, b = (j & 1) ? v.w : v.y;
    const int row0 = wg * 64 + w * 16;
    const uint32_t stg = sb + STG + row0 * 128;
    const uint32_t stw = stg + (lane & 15) * 128 + (((lane >> 4) ^ (lane & 7)) << 4);
    const uint32_t aw = (uint32_t)mkdesc(1024 + wg * 8192, 16, 0);
    constexpr uint32_t bw = (1024 + 16384) / 16 + (8192 / 16 << 16);
    uint32_t x1[32];
    {
      float acc[64];
      int st = 0, prev = 0; uint32_t ph = 0;
#pragma unroll 1
      for (int k = 0; k < 64 - GT; k++) {
        ffn_issue<128>(acc, full + st * 8, ph, aw + SL(st) * 2048, bw + SL(st) * 2048, k == 0);
        if (tid == 0 && (k & 7) == 0) FT(3 + (k >> 3));
        if (tid == 0 && k > 0 && k < 8) FT(19 + k);
        WG_WAIT(1);
        ffn_release(leader && k, emp + prev * 8);
        prev = st;
        if (++st == 6) { st = 0; ph ^= 1; }
      }
      WG_WAIT(0);
      ffn_release(leader, emp + prev * 8);
      acc_fence<64>(acc);
      asm volatile("setmaxnreg.inc.sync.aligned.u32 232;");
      PH(7); if (tid == 0) { FT(11); FC(38); }
      mbar_wait(xbar, 0);
      float s0 = 0, s1 = 0, q0 = 0, q1 = 0;
      uint4 pa;
#pragma unroll
      for (int j = 0; j < 8; j++) {
        uint32_t xv[4];
        ldsm4(xv, (stw ^ ((j & 3) * 32)) + (j >> 2) * 16384);
        PRM2(pa, g0, g1, 0)
        float* d = acc + j * 8;
#pragma unroll
        for (int e = 0; e < 4; e++) {
          const uint32_t g = e < 2 ? g0 : g1;
          x1[j * 4 + e] = pk(fmaf(blo(g), d[e * 2], blo(xv[e])), fmaf(bhi(g), d[e * 2 + 1], bhi(xv[e])));
          d[e * 2] = blo(x1[j * 4 + e]); d[e * 2 + 1] = bhi(x1[j * 4 + e]);
        }
        s0 += (d[0] + d[1]) + (d[4] + d[5]);
        s1 += (d[2] + d[3]) + (d[6] + d[7]);
      }
      s0 += __shfl_xor_sync(~0u, s0, 1); s1 += __shfl_xor_sync(~0u, s1, 1);
      s0 += __shfl_xor_sync(~0u, s0, 2); s1 += __shfl_xor_sync(~0u, s1, 2);
      s0 *= 1.f / 128; s1 *= 1.f / 128;
#pragma unroll
      for (int j = 0; j < 16; j++) {
        float* d = acc + j * 4;
        d[0] -= s0; d[1] -= s0; d[2] -= s1; d[3] -= s1;
        q0 += d[0] * d[0] + d[1] * d[1]; q1 += d[2] * d[2] + d[3] * d[3];
      }
      q0 += __shfl_xor_sync(~0u, q0, 1); q1 += __shfl_xor_sync(~0u, q1, 1);
      q0 += __shfl_xor_sync(~0u, q0, 2); q1 += __shfl_xor_sync(~0u, q1, 2);
      uint4* sp = g_stat + (rb * 128 + row0) * 4 + (lane >> 2);
      if (q == 0) stg_b128(sp + nb * 8, U_(s0), min(U_(q0), 0xfffffffeu), U_(s1), U_(q1));
      if (tid == 0) FT(12);
#pragma unroll
      for (int j = 0; j < 8; j++) {
        PRM2(pa, c0, c1, 256)
        float* d = acc + j * 8;
        d[0] *= blo(c0); d[1] *= bhi(c0); d[2] *= blo(c0); d[3] *= bhi(c0);
        d[4] *= blo(c1); d[5] *= bhi(c1); d[6] *= blo(c1); d[7] *= bhi(c1);
      }
      acc_fence<64>(acc);
      uint4 r0, r1;
      int it = 0;
      while (true) {
        r0 = ldg_b128(sp + q * 16); r1 = ldg_b128(sp + q * 16 + 8);
        if (__all_sync(~0u, r0.y != ~0u && r1.y != ~0u)) break;
        if (++it > SPIN_LIMIT) __trap();
      }
      if (tid == 0) FT(13);
      float m0 = F_(r0.x) + F_(r1.x), m1 = F_(r0.z) + F_(r1.z);
      m0 += __shfl_xor_sync(~0u, m0, 1); m1 += __shfl_xor_sync(~0u, m1, 1);
      m0 += __shfl_xor_sync(~0u, m0, 2); m1 += __shfl_xor_sync(~0u, m1, 2);
      m0 *= 0.125f; m1 *= 0.125f;
      float a = F_(r0.x) - m0, b = F_(r1.x) - m0, c = F_(r0.z) - m1, d = F_(r1.z) - m1;
      float v0 = F_(r0.y) + F_(r1.y) + 128.f * (a * a + b * b);
      float v1 = F_(r0.w) + F_(r1.w) + 128.f * (c * c + d * d);
      v0 += __shfl_xor_sync(~0u, v0, 1); v1 += __shfl_xor_sync(~0u, v1, 1);
      v0 += __shfl_xor_sync(~0u, v0, 2); v1 += __shfl_xor_sync(~0u, v1, 2);
      const float rs0 = rsqrtf(v0 * (1.f / 1024) + 1e-5f), rs1 = rsqrtf(v1 * (1.f / 1024) + 1e-5f);
      const float k0 = (s0 - m0) * rs0, k1 = (s1 - m1) * rs1;
      uint4 pc[4], ph_[4];
#pragma unroll
      for (int j = 0; j < 8; j++) {
        if (j == 0) {
#pragma unroll
          for (int i = 0; i < 4; i++) { pc[i] = lds4(prm + 256 + i * 64); ph_[i] = lds4(prm + 512 + i * 64); }
        }
        const uint32_t c0 = (j & 1) ? pc[j >> 1].z : pc[j >> 1].x, c1 = (j & 1) ? pc[j >> 1].w : pc[j >> 1].y;
        const uint32_t h0 = (j & 1) ? ph_[j >> 1].z : ph_[j >> 1].x, h1 = (j & 1) ? ph_[j >> 1].w : ph_[j >> 1].y;
        const float* d = acc + j * 8;
        stsm4((stw ^ ((j & 3) * 32)) + (j >> 2) * 16384,
              pk(fmaf(d[0], rs0, fmaf(k0, blo(c0), blo(h0))), fmaf(d[1], rs0, fmaf(k0, bhi(c0), bhi(h0)))),
              pk(fmaf(d[2], rs1, fmaf(k1, blo(c0), blo(h0))), fmaf(d[3], rs1, fmaf(k1, bhi(c0), bhi(h0)))),
              pk(fmaf(d[4], rs0, fmaf(k0, blo(c1), blo(h1))), fmaf(d[5], rs0, fmaf(k0, bhi(c1), bhi(h1)))),
              pk(fmaf(d[6], rs1, fmaf(k1, blo(c1), blo(h1))), fmaf(d[7], rs1, fmaf(k1, bhi(c1), bhi(h1)))));
      }
      FENCE_ASYNC_SMEM();
      __syncwarp();
      asm volatile("{.reg .pred p; elect.sync _|p, 0xffffffff; @p cp.async.bulk.global.shared::cta.bulk_group [%0],[%1],2048;\n"
                   "@p cp.async.bulk.global.shared::cta.bulk_group [%0+16384],[%1+16384],2048; cp.async.bulk.commit_group;}"
                   ::"l"(g_h2 + (size_t)(rb * 16 + nb * 2) * 1024 + row0 * 8), "r"(stg) : "memory");
      if (wg) BAR_SYNC(2, 128); else BAR_SYNC(3, 128);
    }
    PH(8); if (tid == 0) FT(14);
    const uint4* dst = UBASE + nb * 7 * 1024 + row0 * 8;
    int st = (64 - GT) % 6, prev = 0, flip = 0; uint32_t ph = (64 - GT) / 6 & 1, bs = sb + PRM + 1280 + q * 32;
#define NEXT() do { prev = st; if (++st == 6) { st = 0; ph ^= 1; } } while (0)
#define QUAD(N, acc, u, t, off, first) \
_Pragma("unroll") \
      for (int i = 0; i < 4; i++) { \
        const uint2 b = lds2u(bs + i * 8); \
        ffn_issue<N>(acc, full + st * 8, ph, aw + (off), bw + (off), i == 0 && (first)); \
        if (i == 0 && (t)) { ffn_store(stg + flip, dst); flip ^= 16384; dst += 1024; } \
        if (i == 3 && ((t) == 2 || (t) == 4)) ffn_done(cnt + (t) * 16); \
        WG_WAIT(1); \
        ffn_release(leader, emp + prev * 8); \
        NEXT(); \
        ffn_gelu(u, i, b, stw + flip, mp.zero[0]); \
      } \
      bs += 128;
    uint32_t u0[64], u1[48];
    {
      float acc[128];
#pragma unroll 1
      for (int k = 0; k < 16; k++) {
        ffn_issue<256>(acc, full + st * 8, ph, aw + (k < 2 ? STG / 16 + k * 1024 : (k & 3) * 3072), bw + (k & 3) * 3072, k == 0);
        if (tid == 0 && (k & 7) == 0) FT(15 + (k >> 3));
        if (k == 0) { ffn_done(cnt); if (tid == 0) FT(32); }
        if (FTS_ != 2 && tid == 0 && k && k < 5) FT(59 + k);
        WG_WAIT(1);
        ffn_release(leader && k, emp + prev * 8);
        NEXT();
      }
      WG_WAIT(0);
      acc_fence<128>(acc);
#pragma unroll
      for (int i = 0; i < 64; i++) u0[i] = pk(acc[2 * i], acc[2 * i + 1]);
    }
    PH(9); if (tid == 0) FT(17);
    {
      float acc[96];
#pragma unroll 1
      for (int t = 0; t < 4; t++) {
        if (FTS_ != 2 && tid == 0) FT(42 + t);
        QUAD(192, acc, u0, t, i * 3072, t == 0)
      }
      WG_WAIT(0);
      acc_fence<96>(acc);
#pragma unroll
      for (int i = 0; i < 48; i++) u1[i] = pk(acc[2 * i], acc[2 * i + 1]);
    }
    {
      float acc[64];
#pragma unroll 1
      for (int t = 4; t < 7; t++) {
        if (FTS_ != 2 && tid == 0) FT(42 + t);
        QUAD(128, acc, u1, t, SL(st) * 2048, t == 4)
      }
      uint4 pg[4], pb[4];
#pragma unroll
      for (int i = 0; i < 4; i++) { pg[i] = lds4(prm + 768 + i * 64); pb[i] = lds4(prm + 1024 + i * 64); }
#pragma unroll 1
      for (int k = 12; k < 56; k++) {
        if (FTS_ != 2 && tid == 0 && (k & 3) == 0) FT(46 + (k >> 2));
        ffn_issue<128>(acc, full + st * 8, ph, aw + SL(st) * 2048, bw + SL(st) * 2048, false);
        if (k == 12) ffn_store(stg + flip, dst);
        if (k == 16) ffn_done(cnt + 96);
        WG_WAIT(1);
        ffn_release(leader, emp + prev * 8);
        NEXT();
      }
      WG_WAIT(0);
      acc_fence<64>(acc);
      PH(13); if (tid == 0) { FT(30); FC(39); }
#pragma unroll
      for (int j = 0; j < 8; j++) {
        const uint32_t g0 = (j & 1) ? pg[j >> 1].z : pg[j >> 1].x, g1 = (j & 1) ? pg[j >> 1].w : pg[j >> 1].y;
        const uint32_t h0 = (j & 1) ? pb[j >> 1].z : pb[j >> 1].x, h1 = (j & 1) ? pb[j >> 1].w : pb[j >> 1].y;
        const float* d = acc + j * 8;
        const uint32_t* xv = x1 + j * 4;
        stsm4((stw ^ ((j & 3) * 32)) + (j >> 2) * 16384,
              pk(blo(xv[0]) + blo(g0) * (d[0] + blo(h0)), bhi(xv[0]) + bhi(g0) * (d[1] + bhi(h0))),
              pk(blo(xv[1]) + blo(g0) * (d[2] + blo(h0)), bhi(xv[1]) + bhi(g0) * (d[3] + bhi(h0))),
              pk(blo(xv[2]) + blo(g1) * (d[4] + blo(h1)), bhi(xv[2]) + bhi(g1) * (d[5] + bhi(h1))),
              pk(blo(xv[3]) + blo(g1) * (d[6] + blo(h1)), bhi(xv[3]) + bhi(g1) * (d[7] + bhi(h1))));
        if ((j & 3) == 3) {
          FENCE_ASYNC_SMEM();
          __syncwarp();
          asm volatile("{.reg .pred p; elect.sync _|p, 0xffffffff; @p cp.async.bulk.tensor.2d.global.shared::cta.bulk_group [%0,{%1,%2}],[%3];}"
                       ::"l"(&mp.out), "r"(nb * 128 + (j >> 2) * 64), "r"(rb * 128 + row0), "r"(stg + (j >> 2) * 16384) : "memory");
          if (j == 3) { SCHED_FENCE(47); acc_fence<32>(acc + 32); }
        }
      }
      BULK_COMMIT(); BULK_WAIT_READ(0);
    }
    PH(14); if (tid == 0) FT(31);
  }
}

typedef CUresult (*EncFn)(CUtensorMap*, CUtensorMapDataType, cuuint32_t, void*, const cuuint64_t*, const cuuint64_t*, const cuuint32_t*,
                          const cuuint32_t*, CUtensorMapInterleave, CUtensorMapSwizzle, CUtensorMapL2promotion, CUtensorMapFloatOOBfill);
static void map2d(EncFn enc, CUtensorMap* m, const void* p, int rows, int cols, int boxRows) {
  cuuint64_t d[2] = {(cuuint64_t)cols, (cuuint64_t)rows}, s[1] = {(cuuint64_t)cols * 2};
  cuuint32_t b[2] = {64, (cuuint32_t)boxRows}, e[2] = {1, 1};
  enc(m, CU_TENSOR_MAP_DATA_TYPE_BFLOAT16, 2, (void*)p, d, s, b, e, CU_TENSOR_MAP_INTERLEAVE_NONE, CU_TENSOR_MAP_SWIZZLE_128B,
      CU_TENSOR_MAP_L2_PROMOTION_L2_128B, CU_TENSOR_MAP_FLOAT_OOB_FILL_NONE);
}
static void map3d(EncFn enc, CUtensorMap* m, const void* p, int rows, int cols, int nch) {
  cuuint64_t d[3] = {64, (cuuint64_t)rows, (cuuint64_t)(cols / 64)}, s[2] = {(cuuint64_t)cols * 2, 128};
  cuuint32_t b[3] = {64, 64, (cuuint32_t)nch}, e[3] = {1, 1, 1};
  enc(m, CU_TENSOR_MAP_DATA_TYPE_BFLOAT16, 3, (void*)p, d, s, b, e, CU_TENSOR_MAP_INTERLEAVE_NONE, CU_TENSOR_MAP_SWIZZLE_128B,
      CU_TENSOR_MAP_L2_PROMOTION_L2_128B, CU_TENSOR_MAP_FLOAT_OOB_FILL_NONE);
}

extern "C" void kernel_launch(void* const* d_in, const int* in_sizes, int n_in, void* d_out, int out_size) {
  const bf16* x = (const bf16*)d_in[0];
  const bf16* mem0 = (const bf16*)d_in[1];
  void* fn = nullptr;
  cudaDriverEntryPointQueryResult qr;
  cudaGetDriverEntryPoint("cuTensorMapEncodeTiled", &fn, cudaEnableDefault, &qr);
  EncFn enc = (EncFn)fn;
  FfnMaps fm = {};
  map3d(enc, &fm.wo, d_in[5], 4096, 1024, 2);
  map3d(enc, &fm.w1a, d_in[8], 1024, 3584, 4);
  map3d(enc, &fm.w1b, d_in[8], 1024, 3584, 3);
  map3d(enc, &fm.w2, d_in[10], 3584, 1024, 2);
  map2d(enc, &fm.x, x, 2048, 1024, 128);
  map2d(enc, &fm.out, d_out, 2048, 1024, 16);
  map3d(enc, &fm.wo4, d_in[5], 4096, 1024, 4);
  {
    void* xp = nullptr;
    cudaGetSymbolAddress(&xp, g_xp);
    map2d(enc, &fm.xp, xp, 2048, 1024, 128);
    map2d(enc, &fm.xps, xp, 2048, 1024, 16);
  }
  RecMaps rm = {};
  map2d(enc, &rm.wq, d_in[2], 1024, 4096, 128);
  map2d(enc, &rm.wk, d_in[3], 1024, 4096, 128);
  map2d(enc, &rm.wv, d_in[4], 1024, 4096, 16);
  map2d(enc, &rm.wo, d_in[5], 4096, 1024, 128);
  map3d(enc, &rm.wm3, d_in[13], 1024, 6144, 8);
  {
    cuuint64_t d[2] = {6144, 1024}, sd[1] = {12288};
    cuuint32_t bi[2] = {256, 32}, e[2] = {1, 1};
    enc(&rm.wm, CU_TENSOR_MAP_DATA_TYPE_BFLOAT16, 2, d_in[13], d, sd, bi, e, CU_TENSOR_MAP_INTERLEAVE_NONE, CU_TENSOR_MAP_SWIZZLE_NONE,
        CU_TENSOR_MAP_L2_PROMOTION_NONE, CU_TENSOR_MAP_FLOAT_OOB_FILL_NONE);
  }
  {
    void* hp = nullptr;
    cudaGetSymbolAddress(&hp, g_h);
    cuuint64_t d[3] = {64, 32, 1024}, sd[2] = {128, 4096};
    cuuint32_t bi[3] = {64, 16, 16}, e[3] = {1, 1, 1};
    enc(&rm.hst, CU_TENSOR_MAP_DATA_TYPE_BFLOAT16, 3, hp, d, sd, bi, e, CU_TENSOR_MAP_INTERLEAVE_NONE, CU_TENSOR_MAP_SWIZZLE_NONE,
        CU_TENSOR_MAP_L2_PROMOTION_NONE, CU_TENSOR_MAP_FLOAT_OOB_FILL_NONE);
  }
  {
    void* ar = nullptr;
    cudaGetSymbolAddress(&ar, g_ar);
    cuuint64_t d[2] = {512, 160}, sd[1] = {1024};
    cuuint32_t bi[2] = {64, 40}, e[2] = {1, 1};
    enc(&rm.ari, CU_TENSOR_MAP_DATA_TYPE_BFLOAT16, 2, ar, d, sd, bi, e, CU_TENSOR_MAP_INTERLEAVE_NONE, CU_TENSOR_MAP_SWIZZLE_NONE,
        CU_TENSOR_MAP_L2_PROMOTION_NONE, CU_TENSOR_MAP_FLOAT_OOB_FILL_NONE);
  }
  cudaFuncSetAttribute(k_ffn, cudaFuncAttributeMaxDynamicSharedMemorySize, ffn::SMEM);
  cudaFuncSetAttribute(k_rec, cudaFuncAttributeMaxDynamicSharedMemorySize, rec::SMEM);
  char* xc = nullptr;
  cudaGetSymbolAddress((void**)&xc, g_xc);
  xc += (0 - (uintptr_t)xc) & 0x3FFFF;
  {
    cuuint64_t d[5] = {256, 4, 2, 2, 1024}, sd[4] = {rec::XC, 512, 2048, 8192};
    cuuint32_t bi[5] = {256, 4, 2, 1, 1}, e[5] = {1, 1, 1, 1, 1};
    enc(&rm.vx, CU_TENSOR_MAP_DATA_TYPE_BFLOAT16, 5, xc, d, sd, bi, e, CU_TENSOR_MAP_INTERLEAVE_NONE, CU_TENSOR_MAP_SWIZZLE_NONE,
        CU_TENSOR_MAP_L2_PROMOTION_NONE, CU_TENSOR_MAP_FLOAT_OOB_FILL_NONE);
  }
  cudaStream_t st = cudaStreamPerThread;
  int dF = 450, dA = 2700, dS = 300, dM = 120, dG = 350, dP = 24, dX = 48, dD = 350, dZ = 0, dZ2 = 1, dV = 370, dX2 = 60;
  k_rec<<<132, 512, rec::SMEM, st>>>(rm, mem0, x, (const bf16*)d_in[12], (const bf16*)d_in[13], (const bf16*)d_in[5], xc, dF, dA, dS, dM, dG, dP, dX, dD, dZ, dZ2, dV, dX2);
  cudaLaunchConfig_t cfg = {};
  cfg.gridDim = dim3(132); cfg.blockDim = dim3(384); cfg.dynamicSmemBytes = ffn::SMEM; cfg.stream = st;
  cudaLaunchAttribute at[1];
  at[0].id = cudaLaunchAttributeProgrammaticStreamSerialization;
  at[0].val.programmaticStreamSerializationAllowed = 1;
  cfg.attrs = at; cfg.numAttrs = 1;
  cudaLaunchKernelEx(&cfg, k_ffn, fm, (const bf16*)d_in[9], (const bf16*)d_in[11], (const char*)x);
}
```
